```python
import torch

def _softmax(x, axis=-1):
    return torch.softmax(x, dim=axis)
def _gelu(x):
    return torch.nn.functional.gelu(x, approximate="tanh")
def _silu(x):
    return torch.nn.functional.silu(x)
def _sigmoid(x):
    return torch.sigmoid(x)
def _layernorm(x, axis=-1, eps=1e-5):
    m = x.mean(dim=axis, keepdim=True)
    v = x.var(dim=axis, keepdim=True, unbiased=False)
    return (x - m) / torch.sqrt(v + eps)
def _scatter_add(tgt, idx, src, axis=0):
    return tgt.clone().index_add_(axis, idx, src)
def _segment_sum(src, seg, n):
    out = torch.zeros((n,) + src.shape[1:], dtype=src.dtype)
    return out.index_add_(0, seg, src)
def _pad(x, pw):
    flat = tuple(v for pair in reversed(pw) for v in pair)
    return torch.nn.functional.pad(x, flat)

kernel_name = 'standalone__winograd__vision'

def setup_inputs():

    _w = (lambda a: (lambda t: t.to(torch.bfloat16) if t.is_floating_point() else t)(torch.as_tensor(a)))
    H = W = 512 // 2 * 2
    C = 192
    return {
        "x": _w((lambda *s: torch.randn(*s, dtype=torch.bfloat16) * 0.05)(1, H, W, C)),
        "w": _w((lambda *s: torch.randn(*s, dtype=torch.bfloat16) * 0.05)(3, 3, C, C)),
    }

def reference(x, w):
    N, H, W, C = x.shape
    K = w.shape[-1]
    G  = torch.as_tensor([[1.0,0.0,0.0],[0.5,0.5,0.5],[0.5,-0.5,0.5],[0.0,0.0,1.0]], dtype=x.dtype)
    Bt = torch.as_tensor([[1.0,0.0,-1.0,0.0],[0.0,1.0,1.0,0.0],[0.0,-1.0,1.0,0.0],[0.0,1.0,0.0,-1.0]], dtype=x.dtype)
    At = torch.as_tensor([[1.0,1.0,1.0,0.0],[0.0,1.0,-1.0,-1.0]], dtype=x.dtype)
    U = torch.einsum("ar,rsck,bs->abck", G, w, G)
    xp = _pad(x, ((0,0),(1,1),(1,1),(0,0)))
    nH, nW = H // 2, W // 2
    patches = []
    for i in range(4):
        for j in range(4):
            patches.append(xp[:, i:i + 2 * nH:2, j:j + 2 * nW:2, :])
    d = torch.stack(patches).reshape(4, 4, N * nH * nW, C)
    V = torch.einsum("ai,ijpc,bj->abpc", Bt, d, Bt)
    M = torch.einsum("abck,abpc->abpk", U, V)
    Y = torch.einsum("ma,abpk,nb->pmnk", At, M, At)
    Y = Y.reshape(N, nH, nW, 2, 2, K)
    Y = (lambda x, *d: x.permute(*d))(Y, 0, 1, 3, 2, 4, 5).reshape(N, H, W, K)
    return Y
```

```cpp
#include <cuda_runtime.h>
#include <cuda.h>
#include <cuda_bf16.h>
#include <cuda_fp16.h>
#include <stdint.h>
#include <type_traits>

namespace {

constexpr int IMG = 512;
constexpr int CH = 192;
constexpr int ROWB = IMG * CH * 2;
constexpr int TCOL = 66 * 16;
constexpr int TUNIT = 4 * TCOL;
constexpr int TWG = 12 * TUNIT;
constexpr int RROW = 4 * 64;
constexpr int RSLOT = 8 * RROW;
#define X_NUST 9
constexpr int NRS = X_NUST == 9 ? 2 : 3;
constexpr int UTILE = 192 * 32;
constexpr int NUST = X_NUST;
constexpr int NROUND = 144 / NUST, NFROUND = 72 / NUST;
constexpr int UWG = (NROUND + NFROUND) * NUST * UTILE;
constexpr int SM_U = 0;
constexpr int SM_R = SM_U + 2 * NUST * UTILE;
constexpr int SM_T = 131072 - 1024;
constexpr int SM_BAR = SM_T + 2 * TWG;
static_assert(SM_R + 4 * NRS * RSLOT <= SM_T, "smem");
constexpr int SMEM_BYTES = SM_BAR + 256 + 32 * NUST;
constexpr int NTHREADS = 512;
constexpr int LGA = 3;
constexpr uint32_t BAR_TFULL = SM_BAR, BAR_TEMPTY = SM_BAR + 48, SM_FLAG = SM_BAR + 96, SM_ORG = SM_BAR + 100, SM_EXP = SM_BAR + 240, BAR_RFULL = SM_BAR + 128,
                   BAR_U = SM_BAR + 256;
static_assert(SMEM_BYTES <= 232448 && SM_R % 128 == 0, "smem");
#define UBITS 9
#define PF_START 500
#define PFU 0
#define REG_M 224
#define REG_T 40

__host__ __device__ constexpr int group_of(int q, int c) {
  return q == 0 ? (c < 3 ? 2 * c : 3 * c + 1) : q == 1 ? (c < 3 ? 2 * c + 1 : 3 * c + 2) : q == 2 ? (c < 3 ? 6 + c : 3 * c) : q == 3 ? 18 + c
       : q == 4 ? 24 + (c < 3 ? 2 * c : 3 + c) : 24 + (c < 3 ? 2 * c + 1 : 6 + c);
}
constexpr uint32_t UN_P = 0x141820, UN_Q = 0x252941, UN_R = 0x030A53, UN_S = 0xA98B76, UN_FP = 0xA53820, UN_FQ = 0xB76941;
__host__ __device__ constexpr uint32_t unit(uint32_t tab, int c) { return (tab >> (4 * c)) & 15; }

__device__ __align__(1024) uint8_t g_U[2 * UWG];
__device__ uint32_t g_ready;
#define SPAN(k)
#define TRACE(row, i)

__device__ __forceinline__ uint32_t sample_exp(const void* p, uint32_t stride, int lane) {
  uint32_t m = 0;
#pragma unroll
  for (int i = 0; i < 4; i++) {
    const uint4 v = __ldg(reinterpret_cast<const uint4*>((const char*)p + (lane * 4 + i) * stride));
    m = __vmaxu2(__vmaxu2(m, __vmaxu2(v.x & 0x7FFF7FFFu, v.y & 0x7FFF7FFFu)), __vmaxu2(v.z & 0x7FFF7FFFu, v.w & 0x7FFF7FFFu));
  }
  m = __reduce_max_sync(0xffffffffu, max(m & 0xFFFFu, m >> 16)) >> 7;
  return m ? m : 120;
}
__device__ __forceinline__ uint32_t exp_x(const void* x, int lane) { return min(sample_exp(x, 784400, lane), 138u); }
__device__ __forceinline__ uint32_t exp_w(const void* w, int lane) { return min(sample_exp(w, 5168, lane), 240u); }

constexpr int NFILT = 2 * 6 * 24 * 3;
__device__ __forceinline__ bool filter_task(const __nv_bfloat16* __restrict__ w, uint8_t* U, int t, int lane, uint32_t ew, bool first) {
  const int wg = t & 1, blk = (t >> 1) % 6, co = (t / 12) % 24, s = t / (12 * 24);
  const int k = blk * 32 + ((lane >> 1) & 3) * 8 + (lane >> 3) * 2 + (lane & 1);
  const unsigned short* wp = reinterpret_cast<const unsigned short*>(w) + (s * CH + co * 8) * CH + k;
  float g[3][8];
#pragma unroll
  for (int r = 0; r < 3; r++)
#pragma unroll
    for (int i = 0; i < 8; i++) g[r][i] = __uint_as_float((uint32_t)__ldg(wp + (r * 3 * CH + i) * CH) << 16);
  if (first) asm volatile("bar.sync 11, 288;" ::: "memory");
  asm volatile("ld.shared.u32 %0, [%0];" : "+r"(ew)::"memory");
  const float su = __uint_as_float((249 - ew) << 23);
  const int chunk = co >> 2, k16 = (co >> 1) & 1, oct = co & 1;
  constexpr float na = 1.f / 1.40625f, nb = 32.f / 90.f, nc = 1.f / 4.5f;
  bool ok = true;
#pragma unroll 1
  for (int q = 0; q < 6; q++) {
    float g0, g1, g2;
    if (q < 2) { g0 = wg ? (q ? -nb : nb) : na; g1 = wg ? 2.f * nb : q ? -0.5f * na : 0.5f * na; g2 = wg ? 4.f * g0 : 0.25f * na; }
    else if (q & 1) { g0 = wg ? 0.f : -1.f; g1 = 0.f; g2 = wg ? 1.f : 0.f; }
    else { g1 = q == 2 ? -nc : 0.5f; g0 = g2 = wg ? -g1 : g1; }
    g0 *= su; g1 *= su; g2 *= su;
    const int tile = 6 * group_of(q, chunk) + 3 * k16 + s;
    uint32_t pk[4];
#pragma unroll
    for (int i = 0; i < 4; i++) {
      float v[2];
#pragma unroll
      for (int j = 0; j < 2; j++) {
        v[j] = g0 * g[0][2 * i + j] + g1 * g[1][2 * i + j] + g2 * g[2][2 * i + j];
        ok = ok && fabsf(v[j]) <= 0.49f;
        if (UBITS < 11) v[j] = __uint_as_float((__float_as_uint(v[j]) + (1u << (23 - UBITS))) & ~((1u << (24 - UBITS)) - 1));
      }
      const __half2 t2 = __floats2half2_rn(v[0], v[1]);
      pk[i] = *reinterpret_cast<const uint32_t*>(&t2);
    }
    *reinterpret_cast<uint4*>(U + wg * UWG + tile * UTILE + (blk * 4 + (lane >> 3)) * 256 + oct * 128 + (lane & 7) * 16) = make_uint4(pk[0], pk[1], pk[2], pk[3]);
  }
  return ok;
}

__device__ __forceinline__ uint32_t smem_u32(const void* p) { return (uint32_t)__cvta_generic_to_shared(p); }
__device__ __forceinline__ void mbar_init(uint32_t bar, uint32_t cnt) {
  asm volatile("mbarrier.init.shared::cta.b64 [%0], %1;" ::"r"(bar), "r"(cnt));
}
__device__ __forceinline__ void mbar_expect_tx(uint32_t bar, uint32_t bytes) {
  asm volatile("mbarrier.arrive.expect_tx.shared::cta.b64 _, [%0], %1;" ::"r"(bar), "r"(bytes) : "memory");
}
__device__ __forceinline__ void mbar_wait(uint32_t bar, uint32_t parity) {
  asm volatile(
      "{\n.reg .pred p;\n"
      "WAIT_%=:\n"
      "mbarrier.try_wait.parity.shared::cta.b64 p, [%0], %1;\n"
      "@p bra DONE_%=;\n"
      "bra WAIT_%=;\n"
      "DONE_%=:\n}" ::"r"(bar), "r"(parity) : "memory");
}
__device__ __forceinline__ uint32_t mbar_try(uint32_t bar, uint32_t parity) {
  uint32_t ok;
  asm volatile(
      "{\n.reg .pred p;\n"
      "mbarrier.test_wait.parity.shared::cta.b64 p, [%1], %2;\n"
      "selp.u32 %0, 1, 0, p;\n}" : "=r"(ok) : "r"(bar), "r"(parity) : "memory");
  return ok;
}
__device__ __forceinline__ void mbar_wait_sleep(uint32_t bar, uint32_t parity) {
  asm volatile(
      "{\n.reg .pred p;\n"
      "WAIT_%=:\n"
      "mbarrier.try_wait.parity.shared::cta.b64 p, [%0], %1, 20000;\n"
      "@p bra DONE_%=;\n"
      "bra WAIT_%=;\n"
      "DONE_%=:\n}" ::"r"(bar), "r"(parity) : "memory");
}
#undef mbar_wait
#undef mbar_wait_sleep
__device__ __forceinline__ void arrive_elect(uint32_t bar) {
  asm volatile(
      "{\n.reg .pred p;\n"
      "elect.sync _|p, 0xffffffff;\n"
      "@p mbarrier.arrive.shared::cta.b64 _, [%0];\n}" ::"r"(bar) : "memory");
}
__device__ __forceinline__ void cluster_sync() {
  asm volatile("barrier.cluster.arrive.relaxed.aligned;\nbarrier.cluster.wait.aligned;" ::: "memory");
}
__device__ __forceinline__ void wg_fence() { asm volatile("wgmma.fence.sync.aligned;" ::: "memory"); }
__device__ __forceinline__ void wg_commit() { asm volatile("wgmma.commit_group.sync.aligned;" ::: "memory"); }
template <int N> __device__ __forceinline__ void wg_wait() { asm volatile("wgmma.wait_group.sync.aligned %0;" ::"n"(N) : "memory"); }
template <int LEAD>
__device__ __forceinline__ void wgmma192(uint32_t (&d)[48], uint64_t adesc, uint64_t bdesc, uint32_t acc) {
  asm volatile(
      "{\n.reg .pred p;\n"
      "setp.ne.b32 p, %50, 0;\n"
      "wgmma.mma_async.sync.aligned.m64n192k16.f16.f16.f16 "
      "{%0,%1,%2,%3,%4,%5,%6,%7,%8,%9,%10,%11,%12,%13,%14,%15,%16,%17,%18,%19,%20,%21,%22,%23,%24,%25,%26,%27,%28,%29,%30,%31,%32,%33,%34,%35,%36,%37,%38,%39,%40,%41,%42,%43,%44,%45,%46,%47}, %48, %49, p, 1, 1, 0, 0;\n}\n"
      : "+r"(d[0]),"+r"(d[1]),"+r"(d[2]),"+r"(d[3]),"+r"(d[4]),"+r"(d[5]),"+r"(d[6]),"+r"(d[7]),"+r"(d[8]),"+r"(d[9]),"+r"(d[10]),"+r"(d[11]),"+r"(d[12]),"+r"(d[13]),"+r"(d[14]),"+r"(d[15]),"+r"(d[16]),"+r"(d[17]),"+r"(d[18]),"+r"(d[19]),"+r"(d[20]),"+r"(d[21]),"+r"(d[22]),"+r"(d[23]),"+r"(d[24]),"+r"(d[25]),"+r"(d[26]),"+r"(d[27]),"+r"(d[28]),"+r"(d[29]),"+r"(d[30]),"+r"(d[31]),"+r"(d[32]),"+r"(d[33]),"+r"(d[34]),"+r"(d[35]),"+r"(d[36]),"+r"(d[37]),"+r"(d[38]),"+r"(d[39]),"+r"(d[40]),"+r"(d[41]),"+r"(d[42]),"+r"(d[43]),"+r"(d[44]),"+r"(d[45]),"+r"(d[46]),"+r"(d[47])
      : "l"(adesc), "l"(bdesc), "r"(LEAD ? acc : 1u));
}

__device__ __forceinline__ void sts(uint32_t addr, uint32_t v) { asm volatile("st.shared.u32 [%0], %1;" ::"r"(addr), "r"(v) : "memory"); }
__device__ __forceinline__ void sts(uint32_t addr, uint2 v) { asm volatile("st.shared.v2.u32 [%0], {%1,%2};" ::"r"(addr), "r"(v.x), "r"(v.y) : "memory"); }
__device__ __forceinline__ void lds(uint32_t& v, uint32_t addr) { asm volatile("ld.shared.u32 %0, [%1];" : "=r"(v) : "r"(addr) : "memory"); }
__device__ __forceinline__ void lds(uint2& v, uint32_t addr) { asm volatile("ld.shared.v2.u32 {%0,%1}, [%2];" : "=r"(v.x), "=r"(v.y) : "r"(addr) : "memory"); }
__host__ __device__ constexpr uint32_t h2(uint32_t h) { return h | (h << 16); }
constexpr uint32_t H_2 = h2(0x4000), H_1_2 = h2(0x3800), H_1_4 = h2(0x3400), H_1_8 = h2(0x3000), H_1_16 = h2(0x2C00), H_1_32 = h2(0x2800),
                   H_N4 = h2(0xC400), H_N2 = h2(0xC000), H_N1_2 = h2(0xB800), H_N1_4 = h2(0xB400), H_N17_4 = h2(0xC440), H_1 = h2(0x3C00), H_N1 = h2(0xBC00);
__device__ __forceinline__ uint32_t hfma(uint32_t a, uint32_t b, uint32_t c) {
  uint32_t r; asm("fma.rn.f16x2 %0, %1, %2, %3;" : "=r"(r) : "r"(a), "r"(b), "r"(c)); return r;
}
__device__ __forceinline__ uint32_t hadd(uint32_t a, uint32_t b) { uint32_t r; asm("add.rn.f16x2 %0, %1, %2;" : "=r"(r) : "r"(a), "r"(b)); return r; }
__device__ __forceinline__ uint32_t hsub(uint32_t a, uint32_t b) { uint32_t r; asm("sub.rn.f16x2 %0, %1, %2;" : "=r"(r) : "r"(a), "r"(b)); return r; }
__device__ __forceinline__ uint2 hfma(uint2 a, uint32_t b, uint2 c) { return make_uint2(hfma(a.x, b, c.x), hfma(a.y, b, c.y)); }
__device__ __forceinline__ uint2 hadd(uint2 a, uint2 b) { return make_uint2(hadd(a.x, b.x), hadd(a.y, b.y)); }
__device__ __forceinline__ uint2 hsub(uint2 a, uint2 b) { return make_uint2(hsub(a.x, b.x), hsub(a.y, b.y)); }
__device__ __forceinline__ uint32_t bmul(uint32_t x, uint32_t k) { uint32_t z; asm("mul.rn.bf16x2 %0, %1, %2;" : "=r"(z) : "r"(x), "r"(k)); return z; }
__device__ __forceinline__ void scale(uint32_t& x, uint32_t k, uint32_t& m) { x = bmul(x, k); m |= x; }
__device__ __forceinline__ void scale(uint2& x, uint32_t k, uint32_t& m) {
  x.x = bmul(x.x, k); x.y = bmul(x.y, k);
  asm("lop3.b32 %0, %0, %1, %2, 0xFE;" : "+r"(m) : "r"(x.x), "r"(x.y));
}
__device__ __forceinline__ void tohalf(uint32_t& z) { z = (z & 0x7FFF7FFFu) * 7 + z; }
__device__ __forceinline__ void tohalf(uint2& z) { tohalf(z.x); tohalf(z.y); }
__device__ __forceinline__ bool out_of_range(uint32_t m) {
  m = __reduce_or_sync(0xffffffffu, m & 0x7FFF7FFFu);
  return (m & 0x78007800u) || (m && !(m & 0x06000600u));
}

template <typename V>
__device__ __forceinline__ void planes8(V (&d)[8], uint32_t dp, uint32_t dq, uint32_t dr, uint32_t ds) {
  const V ec = hfma(d[4], H_N17_4, hadd(d[6], d[2])), oc = hfma(d[3], H_N17_4, hadd(d[5], d[1]));
  sts(dr, hadd(ec, oc)); sts(dr + TWG, hsub(ec, oc));
#pragma unroll
  for (int k = 0; k < 6; k++) d[k] = hsub(d[k + 2], d[k]);
  const V ea = hfma(d[2], H_N4, d[4]), oa = hfma(d[1], H_N4, d[3]);
  sts(dp, hfma(oa, H_1_2, ea)); sts(dq, hfma(oa, H_N1_2, ea));
  sts(ds, hfma(hfma(d[0], H_N4, d[2]), H_N1_4, ea)); sts(ds + TWG, hfma(oa, H_N1_4, hfma(d[3], H_N4, d[5])));
  const V eb = hfma(d[2], H_N1_4, d[4]), ob = hfma(d[1], H_N1_4, d[3]);
  sts(dp + TWG, hfma(ob, H_2, eb)); sts(dq + TWG, hfma(ob, H_N2, eb));
}
template <typename V>
__device__ __forceinline__ void planes4(V (&d)[8], uint32_t dp, uint32_t dq) {
  sts(dp, hadd(d[2], d[1])); sts(dp + TWG, hsub(d[2], d[1]));
  sts(dq, hsub(d[2], d[0])); sts(dq + TWG, hsub(d[3], d[1]));
}

__device__ __forceinline__ void planes8(uint32_t (&d)[8], uint32_t (&o)[8]) {
  const uint32_t ec = hfma(d[4], H_N17_4, hadd(d[6], d[2])), oc = hfma(d[3], H_N17_4, hadd(d[5], d[1]));
#pragma unroll
  for (int k = 0; k < 6; k++) d[k] = hsub(d[k + 2], d[k]);
  const uint32_t ea = hfma(d[2], H_N4, d[4]), oa = hfma(d[1], H_N4, d[3]), e0 = hfma(d[0], H_N4, d[2]), o5 = hfma(d[3], H_N4, d[5]);
  const uint32_t eb = hfma(d[2], H_N1_4, d[4]), ob = hfma(d[1], H_N1_4, d[3]);
  o[0] = hfma(oa, H_1_2, ea); o[1] = hfma(oa, H_N1_2, ea); o[2] = hadd(ec, oc); o[3] = hfma(e0, H_N1_4, ea);
  o[4] = hfma(ob, H_2, eb); o[5] = hfma(ob, H_N2, eb); o[6] = hsub(ec, oc); o[7] = hfma(oa, H_N1_4, o5);
}
__device__ __forceinline__ void planes4(uint32_t (&d)[8], uint32_t (&o)[8]) {
  o[0] = hadd(d[2], d[1]); o[1] = hsub(d[2], d[0]); o[4] = hsub(d[2], d[1]); o[5] = hsub(d[3], d[1]);
}

constexpr uint32_t BHI = 256 >> 4, BLO = (128 >> 4) << 16, AHI = 128 >> 4, ALO = (TCOL >> 4) << 16;
__device__ __forceinline__ uint64_t desc(uint32_t lo, uint32_t hi) { uint64_t d; asm("mov.b64 %0, {%1,%2};" : "=l"(d) : "r"(lo), "r"(hi)); return d; }

typedef uint32_t Acc[48];
struct Ctx {
  uint32_t sb;
  uint64_t ad, bd;
  uint32_t b0;
  uint32_t me, ra, tx;
  uint32_t ok;
  bool one;
  uint32_t wg, xs, xr;
  uint32_t w[12];
  uint32_t k, sg;
  const char* o;
  bool on, yes;
};
__device__ __forceinline__ void arrive(uint32_t bar, bool on) {
  asm volatile("{\n.reg .pred p;\nsetp.ne.b32 p, %1, 0;\n@p mbarrier.arrive.shared::cta.b64 _, [%0];\n}" ::"r"(bar), "r"((uint32_t)on) : "memory");
}
template <int S>
__device__ __forceinline__ void release(Ctx& C, uint32_t me) {
  asm volatile(
      "{\n.reg .pred p;\n"
      "setp.eq.b32 p, %1, %4;\n"
      "@p mbarrier.arrive.expect_tx.shared::cta.b64 _, [%0], %2;\n"
      "@p mbarrier.arrive.shared::cluster.b64 _, [%3];\n}" ::"r"(C.b0 + 16 * S), "r"(me), "r"(C.tx), "r"(C.ra), "n"(S) : "memory");
}
template <int SYNC, int ID0, int ID1>
__device__ __forceinline__ void bar(uint32_t wg) {
  if (SYNC) asm volatile("{\n.reg .pred p;\nsetp.ne.b32 p, %0, 0;\n@!p bar.sync %1, 256;\n@p bar.sync %2, 256;\n}" ::"r"(wg), "n"(ID0), "n"(ID1) : "memory");
  else asm volatile("{\n.reg .pred p;\nsetp.ne.b32 p, %0, 0;\n@!p bar.arrive %1, 256;\n@p bar.arrive %2, 256;\n}" ::"r"(wg), "n"(ID0), "n"(ID1) : "memory");
}
__device__ __forceinline__ void sent(Ctx& C) { bar<0, 1, 2>(C.wg); }
__device__ __forceinline__ void await_sent(Ctx& C) { bar<1, 2, 1>(C.wg); }
__device__ __forceinline__ void await_taken(Ctx& C) { bar<1, 3, 4>(C.wg); }
__device__ __forceinline__ void taken(Ctx& C, uint32_t x) { if ((x & blockIdx.y) == 0) bar<0, 4, 3>(C.wg); }

__host__ __device__ constexpr int xoff(int u, int h) { return u * TUNIT + h * 2048; }
template <int B, int OF>
__device__ __forceinline__ void send(const Acc& A, uint32_t addr) {
  asm volatile("st.shared.v4.u32 [%4 + %5], {%0,%1,%2,%3};" ::"r"(A[4 * B]), "r"(A[4 * B + 1]), "r"(A[4 * B + 2]), "r"(A[4 * B + 3]), "r"(addr), "n"(OF) : "memory");
}
template <int B, int OF>
__device__ __forceinline__ void recv(Acc& A, uint32_t addr, bool on) {
  asm volatile("{\n.reg .pred p;\nsetp.ne.b32 p, %6, 0;\n@p ld.shared.v4.u32 {%0,%1,%2,%3}, [%4 + %5];\n}"
               : "+r"(A[4 * B]), "+r"(A[4 * B + 1]), "+r"(A[4 * B + 2]), "+r"(A[4 * B + 3]) : "r"(addr), "n"(OF), "r"((uint32_t)on) : "memory");
}
template <int OF>
__device__ __forceinline__ void fetch4(uint32_t* w, uint32_t addr) {
  asm volatile("ld.shared.v4.u32 {%0,%1,%2,%3}, [%4 + %5];" : "=r"(w[0]), "=r"(w[1]), "=r"(w[2]), "=r"(w[3]) : "r"(addr), "n"(OF) : "memory");
}
template <int I, int N>
__device__ __forceinline__ void add_to(Acc& A, const uint32_t* w, uint32_t sg) {
#pragma unroll
  for (int j = 0; j < N; j++) asm volatile("fma.rn.f16x2 %0, %1, %2, %0;" : "+r"(A[I + j]) : "r"(w[j]), "r"(sg));
}
template <int I, int N>
__device__ __forceinline__ void join(Acc& A, const Acc& B) {
#pragma unroll
  for (int j = I; j < I + N; j++) asm volatile("add.rn.f16x2 %0, %0, %1;" : "+r"(A[j]) : "r"(B[j]));
}
template <int B, int OF>
__device__ __forceinline__ void split(Acc& A, const Acc& Bb, uint32_t* w, uint32_t addr) {
#pragma unroll
  for (int j = 0; j < 4; j++)
    asm volatile("sub.rn.f16x2 %0, %1, %2;\nadd.rn.f16x2 %1, %1, %2;" : "=&r"(w[j]), "+r"(A[4 * B + j]) : "r"(Bb[4 * B + j]));
  asm volatile("st.shared.v4.u32 [%4 + %5], {%0,%1,%2,%3};" ::"r"(w[0]), "r"(w[1]), "r"(w[2]), "r"(w[3]), "r"(addr), "n"(OF) : "memory");
}
#define KORD 1
__host__ __device__ constexpr int pj(int k) { return KORD ? 2 * (k >> 2) + (k & 1) : k >> 1; }
__host__ __device__ constexpr int ph_(int k) { return KORD ? (k >> 1) & 1 : k & 1; }
template <int K>
__device__ __forceinline__ void rows(const Acc& P, Acc& Q, Acc& R, uint32_t* w) {
#pragma unroll
  for (int i = 0; i < 4; i++) {
    const int j = 8 * pj(K) + 2 * i + ph_(K);
    asm volatile(
        "{\n.reg .b32 a, b;\n"
        "fma.rn.f16x2 a, %1, %4, %2;\n fma.rn.f16x2 b, %1, %5, %2;\n fma.rn.f16x2 %1, %1, %6, %2;\n"
        "fma.rn.f16x2 %0, %3, %7, a;\n fma.rn.f16x2 %2, %3, %8, b;\n add.rn.f16x2 %1, %1, %3;\n}"
        : "=r"(w[i]), "+r"(Q[j]), "+r"(R[j]) : "r"(P[j]), "r"(H_1_8), "r"(H_1_2), "r"(H_1_32), "r"(H_1_4), "r"(H_1_16));
  }
}
__device__ __forceinline__ uint32_t tobf(uint32_t h, uint32_t k) {
  uint32_t o;
  asm volatile("{\n.reg .b16 l, u;\n.reg .f32 a, b;\n.reg .b32 t;\nmov.b32 {l, u}, %1;\ncvt.f32.f16 a, l;\ncvt.f32.f16 b, u;\n"
               "cvt.rn.bf16x2.f32 t, b, a;\nmul.rn.bf16x2 %0, t, %2;\n}" : "=r"(o) : "r"(h), "r"(k));
  return o;
}
template <int K>
__device__ __forceinline__ void stg4(const char* o, const uint32_t* r) {
  asm volatile("st.global.cs.v4.u32 [%4 + %5], {%0,%1,%2,%3};" ::"r"(r[0]), "r"(r[1]), "r"(r[2]), "r"(r[3]), "l"(o), "n"(ph_(K) * 8 * CH * 2 + pj(K) * 64) : "memory");
}
template <int K, int NOW = 1>
__device__ __forceinline__ void put(const Acc& A, Ctx& C) {
  uint32_t* w = C.w + (NOW == 2 ? 4 * (K & 1) : 8);
#pragma unroll
  for (int i = 0; i < 4; i++) w[i] = tobf(A[8 * pj(K) + 2 * i + ph_(K)], C.k);
  if (NOW) stg4<K>(C.o, w);
}

#define OUT_R 0x6318C630ull
#define OUT_S 0x0C0300C0300C03ull
#define OUT_M 0x2AAAAA200ull
#define OUT_F 0x281015555ull
#define E0_AT 10
#define E1_AT 16
#define LATE 1
#define AW_SIDE 0
#define ST_EARLY 0
__host__ __device__ constexpr int below(uint64_t m, int n) { return __builtin_popcountll(m & ((1ull << n) - 1)); }
static_assert(below(OUT_R, 36) == 12 && below(OUT_S, 60) == 12 && below(OUT_M, 35) == 12 && below(OUT_F, 36) == 12, "pieces");
static_assert(!(OUT_R & 15) && !(OUT_M & 0x1DFF) && !(OUT_M & (OUT_M << 1)) && below(OUT_M, 15) <= 8 && !(OUT_F & 0x7E000000) && E0_AT >= 9 && E1_AT >= 15, "order");

__host__ __device__ constexpr int r_out(int n) { return n >= 96 && n < 100 ? n - 96 : n == 106 || n == 107 ? n - 102 : -1; }
__host__ __device__ constexpr int r_in(int n) { return n >= 101 && n < 105 ? n - 101 : n == 113 || n == 114 ? n - 109 : -1; }
__host__ __device__ constexpr int d_out(int n) { return n >= 108 && n < 112 ? n - 108 : n == 119 || n == 120 ? n - 115 : -1; }
constexpr uint32_t XU_R = 0x430543, XU_D = 0x542105, XU_F = 0x984210;
template <int N, int FILL>
__device__ __forceinline__ void early(Acc& P, Acc& Q, Acc& R, Acc& S, Ctx& C) {
  if constexpr (ST_EARLY) {
    if constexpr (FILL && N > 36) { if constexpr ((OUT_F >> (N - 37)) & 1) { if (C.on) stg4<below(OUT_F, N - 37)>(C.o, C.w + 8); } }
    if constexpr (!FILL && N > 0 && N < 36) { if constexpr ((OUT_R >> (N - 1)) & 1) { if (C.on) stg4<below(OUT_R, N - 1)>(C.o, C.w + 8); } }
    if constexpr (!FILL && N > 36 && N < 97) { if constexpr ((OUT_S >> (N - 37)) & 1) { if (C.on) stg4<below(OUT_S, N - 37)>(C.o, C.w + 8); } }
    if constexpr (!FILL && N > 109) { if constexpr ((OUT_M >> (N - 110)) & 1) stg4<below(OUT_M, N - 110)>(C.o, C.w + 8); }
  }
  if constexpr (FILL) {
    constexpr int I = N - 61;
    if constexpr (I == 0) await_sent(C);
    if constexpr (I >= 0 && I < 6) { fetch4<xoff(unit(XU_F, I), 0)>(C.w, C.xr); fetch4<xoff(unit(XU_F, I), 1)>(C.w + 4, C.xr); }
  } else {
    if constexpr (!AW_SIDE && (N == 101 || N == 113 || N == 122)) await_sent(C);
    if constexpr (r_in(N) >= 0) { fetch4<xoff(unit(XU_R, r_in(N)), 0)>(C.w, C.xr); fetch4<xoff(unit(XU_R, r_in(N)), 1)>(C.w + 4, C.xr); }
    if constexpr (N == 115 || N == 116 || N == 122) {
      constexpr int I = N == 122 ? 4 : 2 * (N - 115);
      recv<2 * I, xoff(unit(XU_D, I), 0)>(Q, C.xr, C.yes); recv<2 * I + 1, xoff(unit(XU_D, I), 1)>(Q, C.xr, C.yes);
      recv<2 * I + 2, xoff(unit(XU_D, I + 1), 0)>(Q, C.xr, C.yes); recv<2 * I + 3, xoff(unit(XU_D, I + 1), 1)>(Q, C.xr, C.yes);
    }
  }
}
template <int N, int FILL>
__device__ __forceinline__ void side(Acc& P, Acc& Q, Acc& R, Acc& S, Ctx& C) {
  const uint32_t te = C.sb + BAR_TEMPTY;
  if constexpr (FILL) {
    constexpr int I = N - 36, X = N - 54;
    if constexpr ((OUT_F >> I) & 1) { if (C.on) put<below(OUT_F, I), !ST_EARLY>(S, C); }
    if constexpr (X >= 0 && X < 6) { send<2 * X, xoff(unit(XU_F, X), 0)>(P, C.xs); send<2 * X + 1, xoff(unit(XU_F, X), 1)>(P, C.xs); }
    if constexpr (X == 5) sent(C);
    if constexpr (N >= 61 && N < 67) { if (C.yes) add_to<8 * (N - 61), 8>(P, C.w, C.sg); }
  } else if constexpr (N < 36) {
    if constexpr (N == 0) arrive(te + 16, C.one);
    if constexpr (N < 4) { if (C.on) join<12 * N, 12>(S, Q); }
    if constexpr ((OUT_R >> N) & 1) { if (C.on) put<below(OUT_R, N), !ST_EARLY>(R, C); }
    if constexpr (N == 30) arrive(te + 24, C.one);
  } else if constexpr (N < 96) {
    if constexpr ((OUT_S >> (N - 36)) & 1) { if (C.on) put<below(OUT_S, N - 36), !ST_EARLY>(S, C); }
    if constexpr (N == 48) arrive(te + 32, C.one);
    if constexpr (N == 72) arrive(te + 40, C.one);
  } else {
    constexpr int I = N - 108;
    if constexpr (N == 106 || N == 119) await_taken(C);
    if constexpr (AW_SIDE && (N == 100 || N == 112 || N == 121)) await_sent(C);
    if constexpr (r_out(N) >= 0) {
      constexpr int X = r_out(N);
      send<2 * X, xoff(unit(XU_R, X), 0)>(R, C.xs); send<2 * X + 1, xoff(unit(XU_R, X), 1)>(R, C.xs);
    }
    if constexpr (r_in(N) >= 0) { if (C.yes) add_to<8 * r_in(N), 8>(R, C.w, C.sg); }
    if constexpr (d_out(N) >= 0) {
      constexpr int X = d_out(N);
      if (C.yes) { split<2 * X, xoff(unit(XU_D, X), 0)>(P, Q, C.w, C.xs); split<2 * X + 1, xoff(unit(XU_D, X), 1)>(P, Q, C.w + 4, C.xs); }
    }
    if constexpr (N == 99 || N == 111 || N == 120) sent(C);
    if constexpr (N == 104) taken(C, C.w[3] | C.w[7]);
    if constexpr (N == 117) taken(C, Q[3] | Q[7] | Q[11] | Q[15] | Q[19] | Q[23] | Q[27] | Q[31]);
    if constexpr (I == E0_AT) arrive(te, C.one);
    if constexpr (I == E1_AT) arrive(te + 8, C.one && ((Q[35] | Q[39] | Q[43] | Q[47]) & blockIdx.y) == 0);
    if constexpr (I >= 0) {
      if constexpr ((OUT_M >> I) & 1) { if (C.yes) rows<below(OUT_M, I)>(P, Q, R, C.w); }
    }
    if constexpr (I > 0) {
      if constexpr ((OUT_M >> (I - 1)) & 1) {
        if (C.yes) {
#pragma unroll
          for (int i = 0; i < 4; i++) C.w[8 + i] = tobf(C.w[i], C.k);
        }
        if (!ST_EARLY) stg4<below(OUT_M, I - 1)>(C.o, C.w + 8);
      }
    }
  }
}
template <int W, int LEAD, int N0, int FILL, int J = 0>
__device__ __forceinline__ void group(Acc& P, Acc& Q, Acc& R, Acc& S, Ctx& C, uint64_t a) {
  constexpr int N = N0 + J;
  if (!C.ok) mbar_wait(C.b0 + 16 * (N % NUST), (N / NUST) & 1);
  wg_fence();
  wgmma192<LEAD && J == 0>(W == 0 ? P : W == 1 ? Q : W == 2 ? R : S, a + (((J / 3) * 2 * TCOL + (J % 3) * 16) >> 4), C.bd + (N % NUST) * (UTILE >> 4), blockIdx.y);
  wg_commit();
  C.ok = mbar_try(C.b0 + 16 * ((N + 1) % NUST), ((N + 1) / NUST) & 1);
  if constexpr (LATE && N > 0) side<N - 1, FILL && N != 36>(P, Q, R, S, C);
  early<N, FILL>(P, Q, R, S, C);
  wg_wait<1>();
  release<(N + NUST - 1) % NUST>(C, N || C.on ? C.me : 0);
  if constexpr (!LATE) side<N, FILL>(P, Q, R, S, C);
  if constexpr (J < 5) group<W, LEAD, N0, FILL, J + 1>(P, Q, R, S, C, a);
}

__device__ __forceinline__ void fetch(const CUtensorMap* map, uint32_t bytes, uint32_t dst, uint32_t bar, int c, int x, int y, uint64_t pol) {
  asm volatile("{\n.reg .pred p;\nelect.sync _|p, 0xffffffff;\n"
               "@p mbarrier.arrive.expect_tx.shared::cta.b64 _, [%2], %6;\n"
               "@p cp.async.bulk.tensor.3d.shared::cluster.global.mbarrier::complete_tx::bytes.L2::cache_hint [%0], [%1, {%3,%4,%5}], [%2], %7;\n}"
               ::"r"(dst), "l"(map), "r"(bar), "r"(c), "r"(x), "r"(y), "r"(bytes), "l"(pol) : "memory");
}
constexpr uint64_t POL_NORMAL = 0x16F0000000000000ull, POL_FIRST = 0x12F0000000000000ull;

struct Params { uint8_t* U; uint32_t* ready; int lg, ufirst, ustep, nunit, umax, nfill, s0, second, nfirst; uint4 un[12]; };

__global__ void __launch_bounds__(NTHREADS, 1) wino_main(const __grid_constant__ CUtensorMap xmap8, const __grid_constant__ CUtensorMap xmap4,
                                                         const __nv_bfloat16* __restrict__ xin, const __nv_bfloat16* __restrict__ wgt,
                                                         __nv_bfloat16* __restrict__ out, const Params P) {
  extern __shared__ __align__(1024) uint8_t smem[];
  { const uint32_t l = threadIdx.x * gridDim.x + blockIdx.x; if (l < 9 * CH * CH * 2 / 128) asm volatile("prefetch.global.L2 [%0];" ::"l"((const char*)wgt + l * 128u)); }
  const uint32_t sb = smem_u32(smem);
  const int warp = __shfl_sync(0xffffffffu, threadIdx.x >> 5, 0), lane = threadIdx.x & 31;
  const uint32_t cm = (1u << P.lg) - 1, rank = blockIdx.x & cm;
  const int cl = blockIdx.x >> P.lg;
  if (P.nfill == 0) {
    asm volatile("griddepcontrol.wait;" ::: "memory");
    *P.ready = 0;
    return;
  }
  const int nit = min(P.umax, (P.nunit - cl * P.ufirst + P.ustep - 1) / P.ustep), fu = cl % P.nfill;
  auto first = [&](int i) {
    const int u = cl * P.ufirst + i * P.ustep, q = (u * (205 << (P.lg - 1))) >> 12;
    const int st = P.s0 + (i < nit ? q : fu >> (3 - P.lg));
    const int y = i < nit ? ((u - q * (40 >> P.lg)) * 6 << P.lg) + 6 * rank : 240 + ((fu & ((8 >> P.lg) - 1)) * 2 << P.lg) + 2 * rank;
    return (st & 7) * 64 + ((st >> 3) * 256 + y) * IMG;
  };

  auto origin = [&](int i) { int o; asm volatile("ld.shared.u32 %0, [%1];" : "=r"(o) : "r"(sb + SM_ORG + 4 * i)); return o; };
  if (warp == 9 && lane < 7) sts(sb + SM_ORG + 4 * lane, (uint32_t)first(min(lane, nit)));

  const bool C_yes = sb != gridDim.x;
  if (warp == 0) SPAN(0);
  if (warp == 10) {
    sts(sb + SM_EXP, exp_w(wgt, lane));
    if (!P.second) asm volatile("bar.arrive 11, 288;" ::: "memory");
  }
  if (warp == 9) sts(sb + SM_EXP + 4, exp_x(xin, lane));
  if (warp < 8) {
    asm volatile("barrier.cluster.arrive.relaxed.aligned;" ::: "memory");
    if (!P.second) {
      bool ok = true;
      const int t0 = warp * gridDim.x + blockIdx.x;
      if (t0 >= NFILT) asm volatile("bar.sync 11, 288;" ::: "memory");
#pragma unroll 1
      for (int t = t0; t < NFILT; t += 8 * gridDim.x) ok = filter_task(wgt, P.U, t, lane, sb + SM_EXP, t == t0) && ok;
      asm volatile("fence.proxy.async.global;" ::: "memory");
      uint32_t bad;
      asm volatile("{\n.reg .pred p, q;\nsetp.eq.b32 p, %1, 0;\nbar.red.or.pred q, 10, 256, p;\nselp.u32 %0, 65537, 1, q;\n}" : "=r"(bad) : "r"((uint32_t)ok) : "memory");
      if (threadIdx.x == 0) asm volatile("red.release.gpu.global.add.u32 [%0], %1;" ::"l"(P.ready), "r"(bad) : "memory");
      __syncwarp();
      if (warp == 0) SPAN(1);
    }
  }
  if (warp == 8) {
    uint32_t v; asm volatile("ld.volatile.global.u32 %0, [%1];" : "=r"(v) : "l"(P.ready) : "memory");
    if (v < P.nfirst) __nanosleep(100);
  }
  if (threadIdx.x == 320) {
    for (int i = 0; i < 2 * NUST; i++) { mbar_init(sb + BAR_U + 16 * i, 1); mbar_init(sb + BAR_U + 16 * i + 8, cm + 1); }
    for (int i = 0; i < 6; i++) { mbar_init(sb + BAR_TFULL + 8 * i, 5); mbar_init(sb + BAR_TEMPTY + 8 * i, 8); }
    sts(sb + SM_FLAG, 0u);
    asm volatile("fence.mbarrier_init.release.cluster;" ::: "memory");
    for (int i = 0; i < 2 * NUST; i++) mbar_expect_tx(sb + BAR_U + 16 * i, UTILE);
  }
  const uint32_t rbar = __shfl_sync(0xffffffffu, sb + BAR_RFULL + (warp & 3) * 32, 0), rbuf = sb + SM_R + (warp & 3) * (NRS * RSLOT);
  if (warp >= 12) {
    if (lane == 0) {
      for (int i = 0; i < NRS; i++) mbar_init(rbar + 8 * i, 1);
      asm volatile("fence.mbarrier_init.release.cluster;" ::: "memory");
    }
    __syncwarp();
    if (!P.second) __nanosleep(300);
    const int o = first(0);
#pragma unroll
    for (int i = 0; i < NRS; i++)
      fetch(nit ? &xmap8 : &xmap4, nit ? RSLOT : RSLOT / 2, rbuf + i * RSLOT, rbar + 8 * i, 0, (o & 511) - 1 + (warp & 3) * 16 + i * 4, (o >> 9) - 1, POL_NORMAL);
  }
  __syncwarp();
  if (warp >= 8) asm volatile("barrier.cluster.arrive.release.aligned;" ::: "memory");
  asm volatile("barrier.cluster.wait.acquire.aligned;" ::: "memory");
  uint2 ex;
  lds(ex, sb + SM_EXP);
  const uint32_t kin = h2((139 - ex.y) << 7);

  if (warp >= 12) {
    asm volatile("setmaxnreg.dec.sync.aligned.u32 %0;" ::"n"(REG_T));
    const int wi = warp - 12;
    const uint32_t tb = __shfl_sync(0xffffffffu, sb + SM_T + ((lane >> 1) & 3) * TCOL + (wi * 16 + (lane >> 3)) * 16 + (lane & 1) * 8, lane);
    const uint32_t src = rbuf + __shfl_sync(0xffffffffu, lane * 8, lane);
    const uint32_t nb = __shfl_sync(0xffffffffu, lane & blockIdx.y, lane);
    static_assert(NRS == 2, "box q of a chunk lies in slot q & 1 and is followed by the box after the next");
    int o = origin(0), x = (o & 511) - 1 + wi * 16, y = (o >> 9) - 1;
    auto item = [&](auto fill, int i) {
      constexpr int NR = fill.value ? 4 : 8;
      const CUtensorMap* const map = fill.value ? &xmap4 : &xmap8;
      o = origin(i + 1);
      const int xn = (o & 511) - 1 + wi * 16, yn = (o >> 9) - 1;
      uint32_t m = 0;
#pragma unroll 1
      for (uint32_t c = 0; c < 6; c++) {
        const uint4 un = P.un[6 * fill.value + c];
        const bool turn = c == 5, half = fill.value || (turn && i + 1 == nit);
        const CUtensorMap* const map1 = half ? &xmap4 : &xmap8;
        const int c1 = turn ? 0 : c * 32 + 32, x1 = turn ? xn : x, y1 = turn ? yn : y;
        const uint32_t n1 = half ? RSLOT / 2 : RSLOT;
#pragma unroll
        for (int q = 0; q < 4; q++) {
          const uint32_t sl = (q & 1) * RSLOT, rb = rbar + (q & 1) * 8;
          uint2 d[8];
          mbar_wait_sleep(rb, q >> 1);
#pragma unroll
          for (int r = 0; r < NR; r++) lds(d[r], src + sl + r * RROW);
#pragma unroll
          for (int r = 0; r < NR; r++) scale(d[r], kin, m);
          if (q < 2) fetch(map, NR * RROW | (m & nb), rbuf + sl, rb, c * 32, x + 8 + 4 * q, y, c & 1 ? POL_FIRST : POL_NORMAL);
          else if (!fill.value || !turn) fetch(map1, n1 | (m & nb), rbuf + sl, rb, c1, x1 + 4 * q - 8, y1, c & 1 ? POL_NORMAL : POL_FIRST);
#pragma unroll
          for (int r = 0; r < NR; r++) tohalf(d[r]);
          if (q == 0 && (!fill.value || c < 3)) mbar_wait_sleep(sb + BAR_TEMPTY + 8 * c, (i & 1) ^ (c < 2));
          if (q == 0 && wi == 0) TRACE(2, tn);
          const uint32_t t = tb + 64 * q;
          if (fill.value) planes4(d, t + un.x, t + un.y);
          else planes8(d, t + un.x, t + un.y, t + un.z, t + un.w);
        }
        if (turn && out_of_range(m)) asm volatile("red.shared.or.b32 [%0], %1;" ::"r"(sb + SM_FLAG), "r"(1u << i) : "memory");
        asm volatile("fence.proxy.async.shared::cta;" ::: "memory");
        __syncwarp();
        arrive_elect(sb + BAR_TFULL + 8 * c);
      }
      x = xn; y = yn;
    };
#pragma unroll 1
    for (int i = 0; i < nit; i++) item(std::integral_constant<int, 0>(), i);
    item(std::integral_constant<int, 1>(), nit);
    cluster_sync();
  } else if (warp >= 8) {
    asm volatile("setmaxnreg.dec.sync.aligned.u32 24;");
    if (warp < 10) {
      const uint32_t g = warp - 8, s0 = rank ^ (5 * g & cm);
      const uint32_t ring = sb + SM_U + g * (NUST * UTILE), ub = sb + BAR_U + g * (NUST * 16);
#define PFA 5
#define PFB 10
#define PFC 0
      auto ahead = [&](int i, uint32_t sl, int r) {
        const int o = origin(i), y = o >> 9, nr = i < nit ? 6 : 2;
        const char* pp = (const char*)xin + ((uint32_t)o * (CH * 2u) + sl * 128);
        if (r < nr) {
          const char* a = pp + (r * ROWB + (g * 32 + lane) * (CH * 2));
          asm volatile("prefetch.global.L2 [%0];" ::"l"(a));
          if (r == 0 && rank == 0 && y > 0) asm volatile("prefetch.global.L2 [%0 + %1];" ::"l"(a), "n"(-ROWB));
          if (r + 1 == nr && rank == cm && y + nr < IMG) asm volatile("prefetch.global.L2 [%0 + %1];" ::"l"(a), "n"(ROWB));
        }
        if (r == 1 && lane <= nr + 1 && (uint32_t)(y + lane - 1) < IMG && (o & 511) != 448 * g)
          asm volatile("prefetch.global.L2 [%0];" ::"l"(pp + ((lane - 1) * ROWB + (g ? 64 : -1) * (CH * 2))));
      };
      if (warp == 8) {
        uint32_t v, i = 0;
        do { asm volatile("ld.acquire.gpu.global.u32 %0, [%1];" : "=r"(v) : "l"(P.ready) : "memory"); if (++i > 5000000u) __trap(); } while ((v & 0xFFFF) < P.nfirst);
        if (v >> 16) asm volatile("red.shared.or.b32 [%0], %1;" ::"r"(sb + SM_FLAG), "r"(0xFFFFu) : "memory");
        __syncwarp();
        if (P.second && lane == 0 && (atomicAdd(P.ready, 1) & 0xFFFF) == P.nfirst + gridDim.x - 1) *P.ready = 0;
        __syncwarp();
        SPAN(2);
      }
      asm volatile("bar.sync 9, 96;" ::: "memory");
      asm volatile("fence.proxy.async.global;" ::: "memory");
      uint32_t ph = 1;
#pragma unroll 1
      for (int i = 0; i <= nit; i++) {
        const uint8_t* from = P.U + g * UWG + (i < nit ? 0 : NROUND * NUST * UTILE);
#pragma unroll 1
        for (uint32_t t = 0; t < (i < nit ? NROUND : NFROUND); t++, ph ^= 1, from += NUST * UTILE) {
#pragma unroll 1
          for (uint32_t s = s0; s < NUST; s += cm + 1) {
            mbar_wait_sleep(ub + 16 * s + 8, ph);
            asm volatile(
                "{\n.reg .pred p;\n"
                "elect.sync _|p, 0xffffffff;\n"
                "@p cp.async.bulk.shared::cluster.global.mbarrier::complete_tx::bytes.multicast::cluster [%0], [%1], %2, [%4], %3;\n}"
                ::"r"(ring + s * UTILE), "l"(from + s * UTILE), "n"(UTILE), "h"((uint16_t)((2u << cm) - 1)), "r"(ub + 16 * s) : "memory");
            if (s == s0) {
              if (t - PFC < 6) ahead(i, 2, t - PFC);
              if (i < nit && t - PFA < 6) ahead(i + 1, 0, t - PFA);
              if (i < nit && t - PFB < 6) ahead(i + 1, 1, t - PFB);
            }
          }
        }
      }
    } else if (warp == 10) {
      asm volatile("bar.sync 9, 96;" ::: "memory");
      asm volatile("griddepcontrol.launch_dependents;");
    } else {
      const uint32_t tb = sb + SM_T + ((lane >> 2) & 3) * TCOL + (64 + (lane >> 4)) * 16 + (lane & 3) * 4;
      uint32_t iph = 0;
#pragma unroll 1
      for (int i = 0; i <= nit; i++, iph ^= 1) {
        const int o = origin(i), x = (o & 511) + 63 + (lane >> 4), y = (o >> 9) - 1, nr = i < nit ? 8 : 4;
        const char* p = (const char*)xin + (uint32_t)(o + 63 + (lane >> 4)) * (CH * 2u) + (lane & 15) * 4;
        uint32_t m = 0;
#pragma unroll 1
        for (uint32_t c = 0; c < 6; c++, p += 64) {
          uint32_t d[8];
#pragma unroll
          for (int r = 0; r < 8; r++) {
            d[r] = 0;
            if (x < IMG && (uint32_t)(y + r) < IMG && r < nr) asm volatile("ld.global.nc.u32 %0, [%1];" : "=r"(d[r]) : "l"(p + (r - 1) * ROWB));
          }
#pragma unroll
          for (int r = 0; r < 8; r++) { scale(d[r], kin, m); tohalf(d[r]); }
          if (i < nit || c < 3) mbar_wait_sleep(sb + BAR_TEMPTY + 8 * c, iph ^ (c < 2));
          if (i < nit) planes8(d, tb + unit(UN_P, c) * TUNIT, tb + unit(UN_Q, c) * TUNIT, tb + unit(UN_R, c) * TUNIT, tb + unit(UN_S, c) * TUNIT);
          else planes4(d, tb + unit(UN_FP, c) * TUNIT, tb + unit(UN_FQ, c) * TUNIT);
          if (c == 5 && (m & 0x78007800u)) asm volatile("red.shared.or.b32 [%0], %1;" ::"r"(sb + SM_FLAG), "r"(1u << i) : "memory");
          asm volatile("fence.proxy.async.shared::cta;" ::: "memory");
          __syncwarp();
          arrive_elect(sb + BAR_TFULL + 8 * c);
        }
      }
      if (P.second == 2) asm volatile("griddepcontrol.wait;" ::: "memory");
    }
    __syncwarp();
    cluster_sync();
  } else {
    const uint32_t ek = ex.x + ex.y - 119;
    asm volatile("setmaxnreg.inc.sync.aligned.u32 %0;" ::"n"(REG_M));
    const int wg = warp >> 2;
    Ctx C;
    C.sb = sb; C.wg = wg;
    C.b0 = sb + BAR_U + wg * (NUST * 16);
    C.bd = desc(BLO + (((sb + SM_U + wg * (NUST * UTILE)) & 0x3FFFF) >> 4), BHI);
    C.ad = desc(ALO + (((sb + SM_T + wg * TWG) & 0x3FFFF) >> 4), AHI);
    C.me = __shfl_sync(0xffffffffu, threadIdx.x & 127, lane); C.tx = __shfl_sync(0xffffffffu, lane < NUST ? UTILE : 0, lane);
    asm volatile("mapa.shared::cluster.u32 %0, %1, %2;" : "=r"(C.ra) : "r"(C.b0 + 16 * lane + 8), "r"((lane ^ 5 * wg) & cm));
    C.ok = 0;
    const uint32_t t16 = __shfl_sync(0xffffffffu, (warp & 3) * 512 + lane * 16, lane);
    C.one = (t16 & 511) == 0;
    C.xs = sb + SM_T + wg * TWG + t16;
    C.xr = sb + SM_T + (wg ^ 1) * TWG + t16;
    C.k = h2(ek << 7); C.sg = wg ? H_1 : H_N1;
    C.yes = C.sb != gridDim.x;
    const int drow = wg ? -2 * ROWB : 2 * ROWB;
    const char* const ob = (const char*)out + (uint32_t)(((warp & 3) * 16 + (lane >> 2)) * CH + (lane & 3) * 8) * 2u;
    C.o = ob;
#pragma unroll
    for (int i = 0; i < 12; i++) C.w[i] = 0;

    Acc A0, A1, A2, A3;
#pragma unroll
    for (int j = 0; j < 48; j++) { A0[j] = 0; A1[j] = 0; A2[j] = 0; A3[j] = 0; }
#define G(W, LEAD, N0, FILL, U) group<W, LEAD, N0, FILL>(A0, A1, A2, A3, C, C.ad + (U) * (TUNIT >> 4))
    uint32_t ph = 0;
#pragma unroll 1
    for (int item = 0;; item++) {
      C.on = item != 0;
      if (P.second && item == 1) {
        const int wait = (5 - nit) * 28000 - 10000;
        uint32_t c0, c;
        asm volatile("mov.u32 %0, %%clock;" : "=r"(c0));
        do { __nanosleep(500); asm volatile("mov.u32 %0, %%clock;" : "=r"(c)); } while ((int)(c - c0) < wait);
      }
      C.ad += item & blockIdx.y; C.bd += item & blockIdx.y;
      mbar_wait(sb + BAR_TFULL, ph);
      G(0, 1, 0, 0, unit(UN_P, 0));
      if (warp == 0 && item == 0) SPAN(10);
      G(1, 1, 6, 0, unit(UN_Q, 0));
      mbar_wait(sb + BAR_TFULL + 8, ph);
      G(0, 0, 12, 0, unit(UN_P, 1)); G(1, 0, 18, 0, unit(UN_Q, 1));
      mbar_wait(sb + BAR_TFULL + 16, ph);
      G(0, 0, 24, 0, unit(UN_P, 2)); G(1, 0, 30, 0, unit(UN_Q, 2));
      C.o -= 2 * drow;
      if (item == nit) break;
      G(2, 1, 36, 0, unit(UN_R, 0)); G(2, 0, 42, 0, unit(UN_R, 1)); G(2, 0, 48, 0, unit(UN_R, 2));
      mbar_wait(sb + BAR_TFULL + 24, ph);
      G(2, 0, 54, 0, unit(UN_R, 3)); G(0, 0, 60, 0, unit(UN_P, 3)); G(1, 0, 66, 0, unit(UN_Q, 3));
      mbar_wait(sb + BAR_TFULL + 32, ph);
      G(2, 0, 72, 0, unit(UN_R, 4)); G(0, 0, 78, 0, unit(UN_P, 4)); G(1, 0, 84, 0, unit(UN_Q, 4));
      mbar_wait(sb + BAR_TFULL + 40, ph);
      G(2, 0, 90, 0, unit(UN_R, 5)); G(0, 0, 96, 0, unit(UN_P, 5)); G(1, 0, 102, 0, unit(UN_Q, 5));
      ph ^= 1;
      C.o = ob + (uint32_t)(origin(item) + (2 + wg) * IMG) * (CH * 2u);
      G(3, 1, 108, 0, unit(UN_S, 0)); G(3, 0, 114, 0, unit(UN_S, 1)); G(3, 0, 120, 0, unit(UN_S, 2));
      G(3, 0, 126, 0, unit(UN_S, 3)); G(3, 0, 132, 0, unit(UN_S, 4)); G(3, 0, 138, 0, unit(UN_S, 5));
      C.o += drow;
      if (warp == 0) SPAN(4 + item);
    }
    mbar_wait(sb + BAR_TFULL + 24, ph);
    G(0, 0, 36, 1, unit(UN_FP, 3));
    mbar_wait(sb + BAR_TFULL + 32, ph);
    G(0, 0, 42, 1, unit(UN_FP, 4));
    mbar_wait(sb + BAR_TFULL + 40, ph);
    G(0, 0, 48, 1, unit(UN_FP, 5));
    G(1, 0, 54, 1, unit(UN_FQ, 3)); G(1, 0, 60, 1, unit(UN_FQ, 4)); G(1, 0, 66, 1, unit(UN_FQ, 5));
#undef G
    wg_wait<0>();
    if (warp == 0) SPAN(9);
    uint32_t redo;
    asm volatile("ld.shared.u32 %0, [%1];" : "=r"(redo) : "r"(sb + SM_FLAG) : "memory");
    if (cl < P.nfill) {
      C.o = ob + (uint32_t)(origin(nit) + wg * IMG) * (CH * 2u);
      join<0, 48>(A1, A0);
      put<0, 2>(A1, C); put<1, 2>(A1, C); put<2, 2>(A1, C); put<3, 2>(A1, C); put<4, 2>(A1, C); put<5, 2>(A1, C);
      put<6, 2>(A1, C); put<7, 2>(A1, C); put<8, 2>(A1, C); put<9, 2>(A1, C); put<10, 2>(A1, C); put<11, 2>(A1, C);
    }
    if (warp == 4) SPAN(3);
    if (ek - 1 > 253) redo = 0xFFFF;
    if (redo) {
      asm volatile("bar.sync 5, 256;" ::: "memory");
      const int k = threadIdx.x;
#pragma unroll 1
      for (int i = 0; i < nit + (cl < P.nfill); i++) {
        if (!((redo >> i) & 1) || k >= CH) continue;
        const int o = origin(i);
#pragma unroll 1
        for (int t = 0; t < (i < nit ? 48 : 16); t++) {
          const int y = (o >> 9) + (t >> 3), x = (o & 511) + (t & 7) * 8;
          float acc[8];
#pragma unroll
          for (int j = 0; j < 8; j++) acc[j] = 0.f;
#pragma unroll 1
          for (int rs = 0; rs < 9; rs++) {
            const int yy = y + rs / 3 - 1, xx = x + rs % 3 - 1;
            if ((uint32_t)yy >= IMG) continue;
#pragma unroll 1
            for (int c = 0; c < CH; c += 2) {
              const float w0 = __bfloat162float(wgt[(rs * CH + c) * CH + k]), w1 = __bfloat162float(wgt[(rs * CH + c + 1) * CH + k]);
#pragma unroll
              for (int j = 0; j < 8; j++) {
                if ((uint32_t)(xx + j) < IMG) {
                  const uint32_t v = __ldg(reinterpret_cast<const uint32_t*>(xin + (yy * IMG + xx + j) * CH + c));
                  acc[j] = fmaf(__uint_as_float(v & 0xFFFF0000u), w1, fmaf(__uint_as_float(v << 16), w0, acc[j]));
                }
              }
            }
          }
#pragma unroll
          for (int j = 0; j < 8; j++) out[(y * IMG + x + j) * CH + k] = __float2bfloat16(acc[j]);
        }
      }
    }
    __syncwarp();
    cluster_sync();
  }
}

typedef CUresult (*EncFn)(CUtensorMap*, CUtensorMapDataType, cuuint32_t, void*, const cuuint64_t*, const cuuint64_t*,
                          const cuuint32_t*, const cuuint32_t*, CUtensorMapInterleave, CUtensorMapSwizzle,
                          CUtensorMapL2promotion, CUtensorMapFloatOOBfill);

}

extern "C" void kernel_launch(void* const* d_in, const int* in_sizes, int n_in, void* d_out, int out_size) {
  const __nv_bfloat16* x = (const __nv_bfloat16*)d_in[0];
  const __nv_bfloat16* w = (const __nv_bfloat16*)d_in[1];
  __nv_bfloat16* out = (__nv_bfloat16*)d_out;

  static EncFn enc = nullptr;
  static void *U = nullptr, *ready = nullptr;
  if (!enc) {
    cudaGetSymbolAddress(&U, g_U);
    cudaGetSymbolAddress(&ready, g_ready);
    void* fn = nullptr; cudaDriverEntryPointQueryResult st;
    cudaGetDriverEntryPoint("cuTensorMapEncodeTiled", &fn, cudaEnableDefault, &st);
    enc = (EncFn)fn;
    cudaFuncSetAttribute(wino_main, cudaFuncAttributeMaxDynamicSharedMemorySize, SMEM_BYTES);
  }
  CUtensorMap xmap[2];
  for (int i = 0; i < 2; i++) {
    cuuint64_t dims[3] = {CH, IMG, IMG};
    cuuint64_t str[2] = {CH * 2, (cuuint64_t)ROWB};
    cuuint32_t box[3] = {32, 4, i ? 4u : 8u};
    cuuint32_t es[3] = {1, 1, 1};
    enc(&xmap[i], CU_TENSOR_MAP_DATA_TYPE_BFLOAT16, 3, (void*)x, dims, str, box, es, CU_TENSOR_MAP_INTERLEAVE_NONE,
        CU_TENSOR_MAP_SWIZZLE_NONE, CU_TENSOR_MAP_L2_PROMOTION_L2_128B, CU_TENSOR_MAP_FLOAT_OOB_FILL_NONE);
  }
  cudaLaunchConfig_t cfg = {};
  cudaLaunchAttribute attr[2];
  cfg.blockDim = dim3(NTHREADS);
  cfg.dynamicSmemBytes = SMEM_BYTES;
  cfg.stream = cudaStreamPerThread;
  attr[0].id = cudaLaunchAttributeClusterDimension;
  attr[0].val.clusterDim.x = 1 << LGA; attr[0].val.clusterDim.y = 1; attr[0].val.clusterDim.z = 1;
  attr[1].id = cudaLaunchAttributeProgrammaticStreamSerialization;
  attr[1].val.programmaticStreamSerializationAllowed = 1;
  cfg.attrs = attr;
  static int nca = 0, ncb = 0;
  if (!nca) {
    int n = 0, n2 = 0;
    cfg.numAttrs = 1;
    cfg.gridDim = dim3(128);
    cudaOccupancyMaxActiveClusters(&n, wino_main, &cfg);
    attr[0].val.clusterDim.x = 2;
    cudaOccupancyMaxActiveClusters(&n2, wino_main, &cfg);
    attr[0].val.clusterDim.x = 1 << LGA;
    nca = n < 1 ? 1 : n > 16 ? 16 : n;
    ncb = n2 - (nca << LGA) / 2;
  }
  cfg.numAttrs = 1;
  cfg.gridDim = dim3(nca << LGA);
  Params P = {(uint8_t*)U, (uint32_t*)ready, LGA, 5, 1, 5 * nca, 5, nca, 0, 0, nca << LGA};
  for (int c = 0; c < 6; c++) {
    P.un[c] = make_uint4(unit(UN_P, c) * TUNIT, unit(UN_Q, c) * TUNIT, unit(UN_R, c) * TUNIT, unit(UN_S, c) * TUNIT);
    P.un[6 + c] = make_uint4(unit(UN_FP, c) * TUNIT, unit(UN_FQ, c) * TUNIT, 0, 0);
  }
  cudaLaunchKernelEx(&cfg, wino_main, xmap[0], xmap[1], x, w, out, P);
  const int nf = 4 * (16 - nca), nb = nf == 0 ? 1 : ncb < nf ? nf : ncb > 5 * nf ? 5 * nf : ncb;
  attr[0].val.clusterDim.x = 2;
  cfg.numAttrs = 2;
  cfg.gridDim = dim3(2 * nb);
  cudaStreamCaptureStatus cap = cudaStreamCaptureStatusNone;
  cudaStreamIsCapturing(cfg.stream, &cap);
  P.lg = 1; P.ufirst = 1; P.ustep = nb; P.nunit = 5 * nf; P.nfill = nf; P.s0 = nca; P.second = cap == cudaStreamCaptureStatusActive ? 1 : 2;
  cudaLaunchKernelEx(&cfg, wino_main, xmap[0], xmap[1], x, w, out, P);
}
```

```cpp
#include <cuda_runtime.h>
#include <cuda.h>
#include <cuda_bf16.h>
#include <cuda_fp16.h>
#include <stdint.h>
#include <type_traits>

namespace {

constexpr int IMG = 512;
constexpr int CH = 192;
constexpr int ROWB = IMG * CH * 2;
constexpr int TCOL = 66 * 16;
constexpr int TUNIT = 4 * TCOL;
constexpr int TWG = 12 * TUNIT;
constexpr int RROW = 4 * 64;
constexpr int RSLOT = 8 * RROW;
#define X_NUST 9
constexpr int NRS = X_NUST == 9 ? 2 : 3;
constexpr int UTILE = 192 * 32;
constexpr int NUST = X_NUST;
constexpr int NROUND = 144 / NUST, NFROUND = 72 / NUST;
constexpr int UWG = (NROUND + NFROUND) * NUST * UTILE;
constexpr int SM_U = 0;
constexpr int SM_R = SM_U + 2 * NUST * UTILE;
constexpr int SM_T = 131072 - 1024;
constexpr int SM_BAR = SM_T + 2 * TWG;
static_assert(SM_R + 4 * NRS * RSLOT <= SM_T, "smem");
constexpr int SMEM_BYTES = SM_BAR + 256 + 32 * NUST + 16;
constexpr int NTHREADS = 512;
constexpr int LGA = 3;
constexpr uint32_t BAR_TFULL = SM_BAR, BAR_TEMPTY = SM_BAR + 48, SM_FLAG = SM_BAR + 96, SM_ORG = SM_BAR + 100, SM_EXP = SM_BAR + 256 + 32 * NUST, BAR_RFULL = SM_BAR + 128,
                   BAR_U = SM_BAR + 256;
static_assert(SMEM_BYTES <= 232448 && SM_R % 128 == 0, "smem");
#define UBITS 8
#define PF_START 500
#define PFU 3
#define NQ 6
#define RAW_DELAY 300
#define PF_FIRST 0
#define NSW 4
#define HOLD2 0
#define PF1 0
#define START4 0
#define PAUSE_A 28000
#define PAUSE_B 10000
#define FAKE128 0
#define PFU_MASK 7
#define PFW 0
#define PFT 1
#define PFP 0
#define PFP_SHARE 12
#define PAUSE_AT 2
#define PFW_N 4
#define REG_M 224
#define REG_T 40

__host__ __device__ constexpr int group_of(int q, int c) {
  return q == 0 ? (c < 3 ? 2 * c : 3 * c + 1) : q == 1 ? (c < 3 ? 2 * c + 1 : 3 * c + 2) : q == 2 ? (c < 3 ? 6 + c : 3 * c) : q == 3 ? 18 + c
       : q == 4 ? 24 + (c < 3 ? 2 * c : 3 + c) : 24 + (c < 3 ? 2 * c + 1 : 6 + c);
}
constexpr uint32_t UN_P = 0x141820, UN_Q = 0x252941, UN_R = 0x030A53, UN_S = 0xA98B76, UN_FP = 0xA53820, UN_FQ = 0xB76941;
__host__ __device__ constexpr uint32_t unit(uint32_t tab, int c) { return (tab >> (4 * c)) & 15; }

__device__ __align__(1024) uint8_t g_U[2 * UWG];
__device__ uint32_t g_ready;
#define SPAN(k)
#define TRACE(row, i)

__device__ __forceinline__ void cluster_wait() { asm volatile("barrier.cluster.wait.acquire.aligned;" ::: "memory"); }
__device__ __forceinline__ uint32_t sample_exp(const char* p, uint32_t stride) {
  uint32_t m = 0;
  uint4 v[4];
#pragma unroll
  for (int i = 0; i < 4; i++)
    asm volatile("ld.global.nc.v4.u32 {%0,%1,%2,%3}, [%4];" : "=r"(v[i].x), "=r"(v[i].y), "=r"(v[i].z), "=r"(v[i].w) : "l"(p + i * stride));
  cluster_wait();
#pragma unroll
  for (int i = 0; i < 4; i++)
    m = __vmaxu2(__vmaxu2(m, __vmaxu2(v[i].x & 0x7FFF7FFFu, v[i].y & 0x7FFF7FFFu)), __vmaxu2(v[i].z & 0x7FFF7FFFu, v[i].w & 0x7FFF7FFFu));
  m = __reduce_max_sync(0xffffffffu, max(m & 0xFFFFu, m >> 16)) >> 7;
  return m ? m : 120;
}

constexpr int NFILT = 2 * 6 * 24 * 3;
__device__ __forceinline__ void made(uint32_t* ready, uint32_t n) {
  asm volatile("fence.proxy.async.global;\nbar.sync 10, 256;" ::: "memory");
  if (threadIdx.x == 0) asm volatile("red.release.gpu.global.add.u32 [%0], %1;" ::"l"(ready), "r"(n) : "memory");
  __syncwarp();
}
__device__ __forceinline__ bool filter_task(const __nv_bfloat16* __restrict__ w, uint8_t* U, int t, int lane, uint32_t ew, bool first, bool last, uint32_t* ready) {
  const int wg = t & 1, blk = (t >> 1) % 6, co = (t / 12) % 24, s = t / (12 * 24);
  const int k = blk * 32 + ((lane >> 1) & 3) * 8 + (lane >> 3) * 2 + (lane & 1);
  const unsigned short* wp = reinterpret_cast<const unsigned short*>(w) + ((wg * 6 + s) * CH + co * 8) * CH + k;
  const int dr = wg ? -3 * CH * CH : 3 * CH * CH;
  uint32_t g[3][8];
#pragma unroll
  for (int r = 0; r < 3; r++)
#pragma unroll
    for (int i = 0; i < 8; i++) asm volatile("ld.global.nc.u16 %0, [%1];" : "=r"(g[r][i]) : "l"(wp + r * dr + i * CH));
  const int chunk = co >> 2;
  uint8_t* const u = U + wg * UWG + (3 * ((co >> 1) & 1) + s) * UTILE + (blk * 4 + (lane >> 3)) * 256 + (co & 1) * 128 + (lane & 7) * 16;
  if (first) { cluster_wait(); asm volatile("bar.sync 11, 288;" ::: "memory"); }
  asm volatile("ld.shared.u32 %0, [%0];" : "+r"(ew)::"memory");
  const float su = __uint_as_float((249 - ew) << 23), low = __uint_as_float(15u << 23);
  const float na = (wg ? 128.f / 90.f : 1.f / 1.40625f) * low, sg = wg ? -1.f : 1.f;
  float v[5][8], m = 0.f;
#pragma unroll
  for (int i = 0; i < 8; i++) {
    const float a = __uint_as_float(g[0][i] << 16) * su, b = __uint_as_float(g[1][i] << 16) * su, c = __uint_as_float(g[2][i] << 16) * su;
    asm("{\n.reg .f32 t;\nmax.NaN.f32 t, %1, %2;\nmax.NaN.f32 %0, %0, %3;\nmax.NaN.f32 %0, %0, t;\n}" : "+f"(m) : "f"(fabsf(a)), "f"(fabsf(b)), "f"(fabsf(c)));
    const float e = fmaf(0.25f, c, a) * na, o = b * (0.5f * na), d = fmaf(a + c, sg, b);
    v[0][i] = e + o; v[1][i] = (e - o) * sg; v[2][i] = d * (low / -4.5f); v[3][i] = a * (-sg * low); v[4][i] = d * (0.5f * low);
  }
#pragma unroll
  for (int q = 0; q < 5; q++) {
    uint32_t pk[4];
#pragma unroll
    for (int i = 0; i < 4; i++) {
      asm("cvt.rn.bf16x2.f32 %0, %1, %2;" : "=r"(pk[i]) : "f"(v[q][2 * i + 1]), "f"(v[q][2 * i]));
      pk[i] += (pk[i] & 0x7FFF7FFFu) * 7;
    }
    *reinterpret_cast<uint4*>(u + 6 * group_of(q, chunk) * UTILE) = make_uint4(pk[0], pk[1], pk[2], pk[3]);
    if (q == 3) *reinterpret_cast<uint4*>(u + 6 * group_of(5, chunk) * UTILE) = make_uint4(pk[0], pk[1], pk[2], pk[3]);
    if (q == 1 && last) made(ready, 1);
  }
  return m < 0.1875f;
}

__device__ __forceinline__ uint32_t smem_u32(const void* p) { return (uint32_t)__cvta_generic_to_shared(p); }
__device__ __forceinline__ void mbar_init(uint32_t bar, uint32_t cnt) {
  asm volatile("mbarrier.init.shared::cta.b64 [%0], %1;" ::"r"(bar), "r"(cnt));
}
__device__ __forceinline__ void mbar_expect_tx(uint32_t bar, uint32_t bytes) {
  asm volatile("mbarrier.arrive.expect_tx.shared::cta.b64 _, [%0], %1;" ::"r"(bar), "r"(bytes) : "memory");
}
__device__ __forceinline__ void mbar_wait(uint32_t bar, uint32_t parity) {
  asm volatile(
      "{\n.reg .pred p;\n"
      "WAIT_%=:\n"
      "mbarrier.try_wait.parity.shared::cta.b64 p, [%0], %1;\n"
      "@p bra DONE_%=;\n"
      "bra WAIT_%=;\n"
      "DONE_%=:\n}" ::"r"(bar), "r"(parity) : "memory");
}
__device__ __forceinline__ uint32_t mbar_try(uint32_t bar, uint32_t parity) {
  uint32_t ok;
  asm volatile(
      "{\n.reg .pred p;\n"
      "mbarrier.test_wait.parity.shared::cta.b64 p, [%1], %2;\n"
      "selp.u32 %0, 1, 0, p;\n}" : "=r"(ok) : "r"(bar), "r"(parity) : "memory");
  return ok;
}
__device__ __forceinline__ void mbar_wait_sleep(uint32_t bar, uint32_t parity) {
  asm volatile(
      "{\n.reg .pred p;\n"
      "WAIT_%=:\n"
      "mbarrier.try_wait.parity.shared::cta.b64 p, [%0], %1, 20000;\n"
      "@p bra DONE_%=;\n"
      "bra WAIT_%=;\n"
      "DONE_%=:\n}" ::"r"(bar), "r"(parity) : "memory");
}
#undef mbar_wait
#undef mbar_wait_sleep
__device__ __forceinline__ void arrive_elect(uint32_t bar) {
  asm volatile(
      "{\n.reg .pred p;\n"
      "elect.sync _|p, 0xffffffff;\n"
      "@p mbarrier.arrive.shared::cta.b64 _, [%0];\n}" ::"r"(bar) : "memory");
}
__device__ __forceinline__ void cluster_sync() {
  asm volatile("barrier.cluster.arrive.relaxed.aligned;\nbarrier.cluster.wait.aligned;" ::: "memory");
}
__device__ __forceinline__ void wg_fence() { asm volatile("wgmma.fence.sync.aligned;" ::: "memory"); }
__device__ __forceinline__ void wg_commit() { asm volatile("wgmma.commit_group.sync.aligned;" ::: "memory"); }
template <int N> __device__ __forceinline__ void wg_wait() { asm volatile("wgmma.wait_group.sync.aligned %0;" ::"n"(N) : "memory"); }
template <int LEAD>
__device__ __forceinline__ void wgmma192(uint32_t (&d)[48], uint64_t adesc, uint64_t bdesc, uint32_t acc) {
  asm volatile(
      "{\n.reg .pred p;\n"
      "setp.ne.b32 p, %50, 0;\n"
      "wgmma.mma_async.sync.aligned.m64n192k16.f16.f16.f16 "
      "{%0,%1,%2,%3,%4,%5,%6,%7,%8,%9,%10,%11,%12,%13,%14,%15,%16,%17,%18,%19,%20,%21,%22,%23,%24,%25,%26,%27,%28,%29,%30,%31,%32,%33,%34,%35,%36,%37,%38,%39,%40,%41,%42,%43,%44,%45,%46,%47}, %48, %49, p, 1, 1, 0, 0;\n}\n"
      : "+r"(d[0]),"+r"(d[1]),"+r"(d[2]),"+r"(d[3]),"+r"(d[4]),"+r"(d[5]),"+r"(d[6]),"+r"(d[7]),"+r"(d[8]),"+r"(d[9]),"+r"(d[10]),"+r"(d[11]),"+r"(d[12]),"+r"(d[13]),"+r"(d[14]),"+r"(d[15]),"+r"(d[16]),"+r"(d[17]),"+r"(d[18]),"+r"(d[19]),"+r"(d[20]),"+r"(d[21]),"+r"(d[22]),"+r"(d[23]),"+r"(d[24]),"+r"(d[25]),"+r"(d[26]),"+r"(d[27]),"+r"(d[28]),"+r"(d[29]),"+r"(d[30]),"+r"(d[31]),"+r"(d[32]),"+r"(d[33]),"+r"(d[34]),"+r"(d[35]),"+r"(d[36]),"+r"(d[37]),"+r"(d[38]),"+r"(d[39]),"+r"(d[40]),"+r"(d[41]),"+r"(d[42]),"+r"(d[43]),"+r"(d[44]),"+r"(d[45]),"+r"(d[46]),"+r"(d[47])
      : "l"(adesc), "l"(bdesc), "r"(LEAD ? acc : 1u));
}

__device__ __forceinline__ void sts(uint32_t addr, uint32_t v) { asm volatile("st.shared.u32 [%0], %1;" ::"r"(addr), "r"(v) : "memory"); }
__device__ __forceinline__ void sts(uint32_t addr, uint2 v) { asm volatile("st.shared.v2.u32 [%0], {%1,%2};" ::"r"(addr), "r"(v.x), "r"(v.y) : "memory"); }
__device__ __forceinline__ void lds(uint32_t& v, uint32_t addr) { asm volatile("ld.shared.u32 %0, [%1];" : "=r"(v) : "r"(addr) : "memory"); }
__device__ __forceinline__ void lds(uint2& v, uint32_t addr) { asm volatile("ld.shared.v2.u32 {%0,%1}, [%2];" : "=r"(v.x), "=r"(v.y) : "r"(addr) : "memory"); }
__host__ __device__ constexpr uint32_t h2(uint32_t h) { return h | (h << 16); }
constexpr uint32_t H_2 = h2(0x4000), H_1_2 = h2(0x3800), H_1_4 = h2(0x3400), H_1_8 = h2(0x3000), H_1_16 = h2(0x2C00), H_1_32 = h2(0x2800),
                   H_N4 = h2(0xC400), H_N2 = h2(0xC000), H_N1_2 = h2(0xB800), H_N1_4 = h2(0xB400), H_N17_4 = h2(0xC440), H_1 = h2(0x3C00), H_N1 = h2(0xBC00);
__device__ __forceinline__ uint32_t hfma(uint32_t a, uint32_t b, uint32_t c) {
  uint32_t r; asm("fma.rn.f16x2 %0, %1, %2, %3;" : "=r"(r) : "r"(a), "r"(b), "r"(c)); return r;
}
__device__ __forceinline__ uint32_t hadd(uint32_t a, uint32_t b) { uint32_t r; asm("add.rn.f16x2 %0, %1, %2;" : "=r"(r) : "r"(a), "r"(b)); return r; }
__device__ __forceinline__ uint32_t hsub(uint32_t a, uint32_t b) { uint32_t r; asm("sub.rn.f16x2 %0, %1, %2;" : "=r"(r) : "r"(a), "r"(b)); return r; }
__device__ __forceinline__ uint2 hfma(uint2 a, uint32_t b, uint2 c) { return make_uint2(hfma(a.x, b, c.x), hfma(a.y, b, c.y)); }
__device__ __forceinline__ uint2 hadd(uint2 a, uint2 b) { return make_uint2(hadd(a.x, b.x), hadd(a.y, b.y)); }
__device__ __forceinline__ uint2 hsub(uint2 a, uint2 b) { return make_uint2(hsub(a.x, b.x), hsub(a.y, b.y)); }
__device__ __forceinline__ uint32_t bmul(uint32_t x, uint32_t k) { uint32_t z; asm("mul.rn.bf16x2 %0, %1, %2;" : "=r"(z) : "r"(x), "r"(k)); return z; }
__device__ __forceinline__ void scale(uint32_t& x, uint32_t k, uint32_t& m) { x = bmul(x, k); m |= x; }
__device__ __forceinline__ void scale(uint2& x, uint32_t k, uint32_t& m) {
  x.x = bmul(x.x, k); x.y = bmul(x.y, k);
  asm("lop3.b32 %0, %0, %1, %2, 0xFE;" : "+r"(m) : "r"(x.x), "r"(x.y));
}
__device__ __forceinline__ void tohalf(uint32_t& z) { z = (z & 0x7FFF7FFFu) * 7 + z; }
__device__ __forceinline__ void tohalf(uint2& z) { tohalf(z.x); tohalf(z.y); }
__device__ __forceinline__ bool out_of_range(uint32_t m) {
  m = __reduce_or_sync(0xffffffffu, m & 0x7FFF7FFFu);
  return (m & 0x78007800u) || (m && !(m & 0x06000600u));
}

#define TMASK 0xFFFFFFFFu
__device__ __forceinline__ void stt(uint32_t a, uint32_t v) { sts(a, v & TMASK); }
__device__ __forceinline__ void stt(uint32_t a, uint2 v) { sts(a, make_uint2(v.x & TMASK, v.y & TMASK)); }
template <typename V>
__device__ __forceinline__ void planes8(V (&d)[8], uint32_t dp, uint32_t dq, uint32_t dr, uint32_t ds) {
  const V ec = hfma(d[4], H_N17_4, hadd(d[6], d[2])), oc = hfma(d[3], H_N17_4, hadd(d[5], d[1]));
  stt(dr, hadd(ec, oc)); stt(dr + TWG, hsub(ec, oc));
#pragma unroll
  for (int k = 0; k < 6; k++) d[k] = hsub(d[k + 2], d[k]);
  const V ea = hfma(d[2], H_N4, d[4]), oa = hfma(d[1], H_N4, d[3]);
  stt(dp, hfma(oa, H_1_2, ea)); stt(dq, hfma(oa, H_N1_2, ea));
  stt(ds, hfma(hfma(d[0], H_N4, d[2]), H_N1_4, ea)); stt(ds + TWG, hfma(oa, H_N1_4, hfma(d[3], H_N4, d[5])));
  const V eb = hfma(d[2], H_N1_4, d[4]), ob = hfma(d[1], H_N1_4, d[3]);
  stt(dp + TWG, hfma(ob, H_2, eb)); stt(dq + TWG, hfma(ob, H_N2, eb));
}
template <typename V>
__device__ __forceinline__ void planes4(V (&d)[8], uint32_t dp, uint32_t dq) {
  stt(dp, hadd(d[2], d[1])); stt(dp + TWG, hsub(d[2], d[1]));
  stt(dq, hsub(d[2], d[0])); stt(dq + TWG, hsub(d[3], d[1]));
}

__device__ __forceinline__ void planes8(uint32_t (&d)[8], uint32_t (&o)[8]) {
  const uint32_t ec = hfma(d[4], H_N17_4, hadd(d[6], d[2])), oc = hfma(d[3], H_N17_4, hadd(d[5], d[1]));
#pragma unroll
  for (int k = 0; k < 6; k++) d[k] = hsub(d[k + 2], d[k]);
  const uint32_t ea = hfma(d[2], H_N4, d[4]), oa = hfma(d[1], H_N4, d[3]), e0 = hfma(d[0], H_N4, d[2]), o5 = hfma(d[3], H_N4, d[5]);
  const uint32_t eb = hfma(d[2], H_N1_4, d[4]), ob = hfma(d[1], H_N1_4, d[3]);
  o[0] = hfma(oa, H_1_2, ea); o[1] = hfma(oa, H_N1_2, ea); o[2] = hadd(ec, oc); o[3] = hfma(e0, H_N1_4, ea);
  o[4] = hfma(ob, H_2, eb); o[5] = hfma(ob, H_N2, eb); o[6] = hsub(ec, oc); o[7] = hfma(oa, H_N1_4, o5);
}
__device__ __forceinline__ void planes4(uint32_t (&d)[8], uint32_t (&o)[8]) {
  o[0] = hadd(d[2], d[1]); o[1] = hsub(d[2], d[0]); o[4] = hsub(d[2], d[1]); o[5] = hsub(d[3], d[1]);
}

constexpr uint32_t BHI = 256 >> 4, BLO = (128 >> 4) << 16, AHI = 128 >> 4, ALO = (TCOL >> 4) << 16;
__device__ __forceinline__ uint64_t desc(uint32_t lo, uint32_t hi) { uint64_t d; asm("mov.b64 %0, {%1,%2};" : "=l"(d) : "r"(lo), "r"(hi)); return d; }

typedef uint32_t Acc[48];
struct Ctx {
  uint32_t sb;
  uint64_t ad, bd;
  uint32_t b0;
  uint32_t me, ra, tx;
  uint32_t ok;
  bool one;
  uint32_t wg, xs, xr, xb, t16;
  uint32_t w[12];
  uint32_t k, sg;
  const char* o;
  bool on, yes;
};
__device__ __forceinline__ void arrive(uint32_t bar, bool on) {
  asm volatile("{\n.reg .pred p;\nsetp.ne.b32 p, %1, 0;\n@p mbarrier.arrive.shared::cta.b64 _, [%0];\n}" ::"r"(bar), "r"((uint32_t)on) : "memory");
}
template <int S>
__device__ __forceinline__ void release(Ctx& C, uint32_t me) {
  asm volatile(
      "{\n.reg .pred p;\n"
      "setp.eq.b32 p, %1, %4;\n"
      "@p mbarrier.arrive.expect_tx.shared::cta.b64 _, [%0], %2;\n"
      "@p mbarrier.arrive.shared::cluster.b64 _, [%3];\n}" ::"r"(C.b0 + 16 * S), "r"(me), "r"(C.tx), "r"(C.ra), "n"(S) : "memory");
}
template <int SYNC, int ID0, int ID1>
__device__ __forceinline__ void bar(uint32_t wg) {
  if (SYNC) asm volatile("{\n.reg .pred p;\nsetp.ne.b32 p, %0, 0;\n@!p bar.sync %1, 256;\n@p bar.sync %2, 256;\n}" ::"r"(wg), "n"(ID0), "n"(ID1) : "memory");
  else asm volatile("{\n.reg .pred p;\nsetp.ne.b32 p, %0, 0;\n@!p bar.arrive %1, 256;\n@p bar.arrive %2, 256;\n}" ::"r"(wg), "n"(ID0), "n"(ID1) : "memory");
}
__device__ __forceinline__ void sent(Ctx& C) { bar<0, 1, 2>(C.wg); }
__device__ __forceinline__ void await_sent(Ctx& C) { bar<1, 2, 1>(C.wg); }
__device__ __forceinline__ void sent2(Ctx& C) { bar<0, 10, 11>(C.wg); }
__device__ __forceinline__ void await_sent2(Ctx& C) { bar<1, 11, 10>(C.wg); }
__device__ __forceinline__ void await_taken(Ctx& C) { bar<1, 3, 4>(C.wg); }
__device__ __forceinline__ void taken(Ctx& C, uint32_t x) { if ((x & blockIdx.y) == 0) bar<0, 4, 3>(C.wg); }

#define BEHIND 1
#define LAND 0
__device__ __forceinline__ void landed(uint32_t x) { if (LAND && (x & blockIdx.y)) __trap(); }
__host__ __device__ constexpr int xoff(int u, int h) { return u * TUNIT + h * 2048; }
template <int B, int OF>
__device__ __forceinline__ void send(const Acc& A, uint32_t addr) {
  asm volatile("st.shared.v4.u32 [%4 + %5], {%0,%1,%2,%3};" ::"r"(A[4 * B]), "r"(A[4 * B + 1]), "r"(A[4 * B + 2]), "r"(A[4 * B + 3]), "r"(addr), "n"(OF) : "memory");
}
template <int B, int OF>
__device__ __forceinline__ void recv(Acc& A, uint32_t addr, bool on) {
  asm volatile("{\n.reg .pred p;\nsetp.ne.b32 p, %6, 0;\n@p ld.shared.v4.u32 {%0,%1,%2,%3}, [%4 + %5];\n}"
               : "+r"(A[4 * B]), "+r"(A[4 * B + 1]), "+r"(A[4 * B + 2]), "+r"(A[4 * B + 3]) : "r"(addr), "n"(OF), "r"((uint32_t)on) : "memory");
}
template <int OF>
__device__ __forceinline__ void fetch4(uint32_t* w, uint32_t addr) {
  asm volatile("ld.shared.v4.u32 {%0,%1,%2,%3}, [%4 + %5];" : "=r"(w[0]), "=r"(w[1]), "=r"(w[2]), "=r"(w[3]) : "r"(addr), "n"(OF) : "memory");
}
template <int I, int N>
__device__ __forceinline__ void add_to(Acc& A, const uint32_t* w, uint32_t sg) {
#pragma unroll
  for (int j = 0; j < N; j++) asm volatile("fma.rn.f16x2 %0, %1, %2, %0;" : "+r"(A[I + j]) : "r"(w[j]), "r"(sg));
}
template <int I, int N>
__device__ __forceinline__ void join(Acc& A, const Acc& B) {
#pragma unroll
  for (int j = I; j < I + N; j++) asm volatile("add.rn.f16x2 %0, %0, %1;" : "+r"(A[j]) : "r"(B[j]));
}
template <int B, int OF>
__device__ __forceinline__ void split(Acc& A, const Acc& Bb, uint32_t* w, uint32_t addr) {
#pragma unroll
  for (int j = 0; j < 4; j++)
    asm volatile("sub.rn.f16x2 %0, %1, %2;\nadd.rn.f16x2 %1, %1, %2;" : "=&r"(w[j]), "+r"(A[4 * B + j]) : "r"(Bb[4 * B + j]));
  asm volatile("st.shared.v4.u32 [%4 + %5], {%0,%1,%2,%3};" ::"r"(w[0]), "r"(w[1]), "r"(w[2]), "r"(w[3]), "r"(addr), "n"(OF) : "memory");
}
#define KORD 1
__host__ __device__ constexpr int pj(int k) { return KORD ? 2 * (k >> 2) + (k & 1) : k >> 1; }
__host__ __device__ constexpr int ph_(int k) { return KORD ? (k >> 1) & 1 : k & 1; }
template <int K>
__device__ __forceinline__ void rows(const Acc& P, Acc& Q, Acc& R, uint32_t* w) {
#pragma unroll
  for (int i = 0; i < 4; i++) {
    const int j = 8 * pj(K) + 2 * i + ph_(K);
    asm volatile(
        "{\n.reg .b32 a, b;\n"
        "fma.rn.f16x2 a, %1, %4, %2;\n fma.rn.f16x2 b, %1, %5, %2;\n fma.rn.f16x2 %1, %1, %6, %2;\n"
        "fma.rn.f16x2 %0, %3, %7, a;\n fma.rn.f16x2 %2, %3, %8, b;\n add.rn.f16x2 %1, %1, %3;\n}"
        : "=r"(w[i]), "+r"(Q[j]), "+r"(R[j]) : "r"(P[j]), "r"(H_1_8), "r"(H_1_2), "r"(H_1_32), "r"(H_1_4), "r"(H_1_16));
  }
}
__device__ __forceinline__ uint32_t tobf(uint32_t h, uint32_t k) {
  uint32_t o;
  asm volatile("{\n.reg .b16 l, u;\n.reg .f32 a, b;\n.reg .b32 t;\nmov.b32 {l, u}, %1;\ncvt.f32.f16 a, l;\ncvt.f32.f16 b, u;\n"
               "cvt.rn.bf16x2.f32 t, b, a;\nmul.rn.bf16x2 %0, t, %2;\n}" : "=r"(o) : "r"(h), "r"(k));
  return o;
}
template <int K>
__device__ __forceinline__ void stg4(const char* o, const uint32_t* r) {
#define STQ ".cs"
  asm volatile("st.global" STQ ".v4.u32 [%4 + %5], {%0,%1,%2,%3};" ::"r"(r[0]), "r"(r[1]), "r"(r[2]), "r"(r[3]), "l"(o), "n"(FAKE128 ? ph_(K) * 8 * CH * 2 + (K & 1) * CH * 2 + (K >> 2) * 128 : ph_(K) * 8 * CH * 2 + pj(K) * 64) : "memory");
}
template <int K, int NOW = 1>
__device__ __forceinline__ void put(const Acc& A, Ctx& C) {
  uint32_t* w = C.w + (NOW == 2 ? 4 * (K & 1) : 8);
#pragma unroll
  for (int i = 0; i < 4; i++) w[i] = tobf(A[8 * pj(K) + 2 * i + ph_(K)], C.k);
  if (NOW) stg4<K>(C.o, w);
}

#define OUT_R 0x252949290ull
#define OUT_S 0x084210842108421ull
#define OUT_M 0x151551540ull
#define OUT_F 0x281015555ull
#define E0_AT 6
#define E1_AT 27
#define LATE 0
#define AW_SIDE 0
#define ST_EARLY 0
__host__ __device__ constexpr int below(uint64_t m, int n) { return __builtin_popcountll(m & ((1ull << n) - 1)); }
static_assert(below(OUT_R, 36) == 12 && below(OUT_S, 60) == 12 && below(OUT_M, 35) == 12 && below(OUT_F, 36) == 12, "pieces");
static_assert(!(OUT_R & 15) && !(OUT_M & 0xC03F) && !(OUT_M & (OUT_M << 1)) && below(OUT_M, 8) <= 1 && below(OUT_M, 12) <= 4 && below(OUT_M, 24) <= 8 && below(OUT_M, 28) <= 9 && !(OUT_F & 0x7E000000) && E0_AT >= 6 && E1_AT >= 27, "order");

__host__ __device__ constexpr int r_out(int n) { return n >= 96 && n < 100 ? n - 96 : n == 124 || n == 125 ? n - 120 : -1; }
__host__ __device__ constexpr int d_out(int n) { return n >= 108 && n < 112 ? n - 108 : n == 122 || n == 123 ? n - 118 : -1; }
__host__ __device__ constexpr int r_in(int n) { return n >= 101 && n < 109 ? n - 101 : n == 130 || n == 131 ? n - 122 : n == 134 || n == 135 ? n - 124 : -1; }
__host__ __device__ constexpr int d_in(int n) { return n >= 112 && n < 120 ? n - 112 : n == 128 || n == 129 ? n - 120 : n == 132 || n == 133 ? n - 122 : -1; }
constexpr uint32_t XU_R = 0x750354, XU_D = 0x425421, XU_F = 0x984210;
template <int N, int FILL>
__device__ __forceinline__ void early(Acc& P, Acc& Q, Acc& R, Acc& S, Ctx& C) {
  if constexpr (ST_EARLY) {
    if constexpr (FILL && N > 36) { if constexpr ((OUT_F >> (N - 37)) & 1) { if (C.on) stg4<below(OUT_F, N - 37)>(C.o, C.w + 8); } }
    if constexpr (!FILL && N > 0 && N < 36) { if constexpr ((OUT_R >> (N - 1)) & 1) { if (C.on) stg4<below(OUT_R, N - 1)>(C.o, C.w + 8); } }
    if constexpr (!FILL && N > 36 && N < 97) { if constexpr ((OUT_S >> (N - 37)) & 1) { if (C.on) stg4<below(OUT_S, N - 37)>(C.o, C.w + 8); } }
    if constexpr (!FILL && N > 109) { if constexpr ((OUT_M >> (N - 110)) & 1) stg4<below(OUT_M, N - 110)>(C.o, C.w + 8); }
  }
  if constexpr (FILL) {
    constexpr int I = N - 61;
    if constexpr (I == 0) await_sent(C);
    if constexpr (I >= 0 && I < 6) { fetch4<xoff(unit(XU_F, I), 0)>(C.w, C.xr); fetch4<xoff(unit(XU_F, I), 1)>(C.w + 4, C.xr); }
  } else {
    if constexpr (N == 101 || N == 116) await_sent(C);
    if constexpr (N == 112 || N == 128) await_sent2(C);
    if constexpr (r_in(N) >= 0) {
      constexpr int B = r_in(N);
      fetch4<xoff(unit(XU_R, B / 2), B & 1)>(C.w + 4, C.xr);
    }
    if constexpr (d_in(N) >= 0) {
      constexpr bool dep = BEHIND && ((OUT_M >> (N - 109)) & 1);
      recv<d_in(N), xoff(unit(XU_D, d_in(N) / 2), d_in(N) & 1)>(Q, dep ? C.xb + (C.t16 | (C.w[3] & blockIdx.y)) : C.xr, C.yes);
    }
  }
}
template <int N, int FILL>
__device__ __forceinline__ void side(Acc& P, Acc& Q, Acc& R, Acc& S, Ctx& C) {
  const uint32_t te = C.sb + BAR_TEMPTY;
  if constexpr (FILL) {
    constexpr int I = N - 36, X = N - 54;
    if constexpr ((OUT_F >> I) & 1) { if (C.on) put<below(OUT_F, I), !ST_EARLY>(S, C); }
    if constexpr (X >= 0 && X < 6) { send<2 * X, xoff(unit(XU_F, X), 0)>(P, C.xs); send<2 * X + 1, xoff(unit(XU_F, X), 1)>(P, C.xs); }
    if constexpr (X == 5) sent(C);
    if constexpr (N >= 61 && N < 67) { if (C.yes) add_to<8 * (N - 61), 8>(P, C.w, C.sg); }
  } else if constexpr (N < 36) {
    if constexpr (N == 0) arrive(te + 16, C.one);
    if constexpr (N < 4) { if (C.on) join<12 * N, 12>(S, Q); }
    if constexpr ((OUT_R >> N) & 1) { if (C.on) put<below(OUT_R, N), !ST_EARLY>(R, C); }
    if constexpr (N == 30) arrive(te + 24, C.one);
  } else if constexpr (N < 96) {
    if constexpr ((OUT_S >> (N - 36)) & 1) { if (C.on) put<below(OUT_S, N - 36), !ST_EARLY>(S, C); }
    if constexpr (N == 48) arrive(te + 32, C.one);
    if constexpr (N == 72) arrive(te + 40, C.one);
  } else {
    constexpr int I = N - 108;
    if constexpr (I > 0) {
      if constexpr ((OUT_M >> (I - 1)) & 1) {
        if (C.yes) {
#pragma unroll
          for (int i = 0; i < 4; i++) C.w[8 + i] = tobf(C.w[i], C.k);
        }
        if (!ST_EARLY) stg4<below(OUT_M, I - 1)>(C.o, C.w + 8);
      }
    }
    if constexpr (I >= 0) {
      if constexpr ((OUT_M >> I) & 1) { if (C.yes) rows<below(OUT_M, I)>(P, Q, R, C.w); }
    }
    if constexpr (N == 110 || N == 122) await_taken(C);
    if constexpr (r_out(N) >= 0) {
      constexpr int X = r_out(N);
      send<2 * X, xoff(unit(XU_R, X), 0)>(R, C.xs); send<2 * X + 1, xoff(unit(XU_R, X), 1)>(R, C.xs);
    }
    if constexpr (r_in(N) >= 0) {
      if (C.yes) {
        add_to<4 * r_in(N), 4>(R, C.w + 4, C.sg);
      }
    }
    if constexpr (d_out(N) >= 0) {
      constexpr int X = d_out(N);
      if (C.yes) { split<2 * X, xoff(unit(XU_D, X), 0)>(P, Q, C.w + 4, C.xs); split<2 * X + 1, xoff(unit(XU_D, X), 1)>(P, Q, C.w, C.xs); }
    }
    if constexpr (N == 99 || N == 111) sent(C);
    if constexpr (N == 109 || N == 125) sent2(C);
    if constexpr (N == 108) taken(C, R[31]);
    if constexpr (N == 120) taken(C, Q[11] | Q[15] | Q[19] | Q[23] | Q[27] | Q[31]);
    if constexpr (I == E0_AT) arrive(te, C.one && ((Q[3] | Q[7]) & blockIdx.y) == 0);
    if constexpr (I == E1_AT) arrive(te + 8, C.one && ((R[47] | Q[35] | Q[39] | Q[43] | Q[47]) & blockIdx.y) == 0);
  }
}
template <int W, int LEAD, int N0, int FILL, int J = 0>
__device__ __forceinline__ void group(Acc& P, Acc& Q, Acc& R, Acc& S, Ctx& C, uint64_t a) {
  constexpr int N = N0 + J;
  if (!C.ok) mbar_wait(C.b0 + 16 * (N % NUST), (N / NUST) & 1);
  wg_fence();
  wgmma192<LEAD && J == 0>(W == 0 ? P : W == 1 ? Q : W == 2 ? R : S, a + (((J / 3) * 2 * TCOL + (J % 3) * 16) >> 4), C.bd + (N % NUST) * (UTILE >> 4), blockIdx.y);
  wg_commit();
  C.ok = mbar_try(C.b0 + 16 * ((N + 1) % NUST), ((N + 1) / NUST) & 1);
  if constexpr (LATE && N > 0) side<N - 1, FILL && N != 36>(P, Q, R, S, C);
  early<N, FILL>(P, Q, R, S, C);
  wg_wait<1>();
  release<(N + NUST - 1) % NUST>(C, N || C.on ? C.me : 0);
  if constexpr (!LATE) side<N, FILL>(P, Q, R, S, C);
  if constexpr (J < 5) group<W, LEAD, N0, FILL, J + 1>(P, Q, R, S, C, a);
}

__device__ __forceinline__ void fetch(const CUtensorMap* map, uint32_t bytes, uint32_t dst, uint32_t bar, int c, int x, int y, uint64_t pol) {
  asm volatile("{\n.reg .pred p;\nelect.sync _|p, 0xffffffff;\n"
               "@p mbarrier.arrive.expect_tx.shared::cta.b64 _, [%2], %6;\n"
               "@p cp.async.bulk.tensor.3d.shared::cluster.global.mbarrier::complete_tx::bytes.L2::cache_hint [%0], [%1, {%3,%4,%5}], [%2], %7;\n}"
               ::"r"(dst), "l"(map), "r"(bar), "r"(c), "r"(x), "r"(y), "r"(bytes), "l"(pol) : "memory");
}
constexpr uint64_t POL_NORMAL = 0x16F0000000000000ull, POL_FIRST = 0x12F0000000000000ull;

struct Params { uint8_t* U; uint32_t* ready; int lg, ufirst, ustep, nunit, umax, nfill, s0, second, nfirst; uint4 un[12]; };

__global__ void __launch_bounds__(NTHREADS, 1) wino_main(const __grid_constant__ CUtensorMap xmap8, const __grid_constant__ CUtensorMap xmap4,
                                                         const __grid_constant__ CUtensorMap xmap1,
                                                         const __nv_bfloat16* __restrict__ xin, const __nv_bfloat16* __restrict__ wgt,
                                                         __nv_bfloat16* __restrict__ out, const Params P) {
  extern __shared__ __align__(1024) uint8_t smem[];
  { const uint32_t l = threadIdx.x * gridDim.x + blockIdx.x; if (l < 9 * CH * CH * 2 / 128) asm volatile("prefetch.global.L2 [%0];" ::"l"((const char*)wgt + l * 128u)); }
  const uint32_t sb = smem_u32(smem);
  const int warp = __shfl_sync(0xffffffffu, threadIdx.x >> 5, 0), lane = threadIdx.x & 31;
  const uint32_t cm = (1u << P.lg) - 1, rank = blockIdx.x & cm;
  const int cl = blockIdx.x >> P.lg;
  if (P.nfill == 0) {
    asm volatile("griddepcontrol.wait;" ::: "memory");
    *P.ready = 0;
    return;
  }
  const int nit = min(P.umax, (P.nunit - cl * P.ufirst + P.ustep - 1) / P.ustep), fu = cl % P.nfill;
  auto first = [&](int i) {
    const int u = cl * P.ufirst + i * P.ustep, q = (u * (205 << (P.lg - 1))) >> 12;
    const int st = P.s0 + (i < nit ? q : fu >> (3 - P.lg));
    const int y = i < nit ? ((u - q * (40 >> P.lg)) * 6 << P.lg) + 6 * rank : 240 + ((fu & ((8 >> P.lg) - 1)) * 2 << P.lg) + 2 * rank;
    return (st & 7) * 64 + ((st >> 3) * 256 + y) * IMG;
  };

  auto origin = [&](int i) { int o; asm volatile("ld.shared.u32 %0, [%1];" : "=r"(o) : "r"(sb + SM_ORG + 4 * i)); return o; };
  if (warp == 11 && lane < 7) sts(sb + SM_ORG + 4 * lane, (uint32_t)first(min(lane, nit)));

  const bool C_yes = sb != gridDim.x;
  if (warp == 0) SPAN(0);
  if (warp != 11) asm volatile("barrier.cluster.arrive.relaxed.aligned;" ::: "memory");
  if (warp == 10) {
    sts(sb + SM_EXP, min(sample_exp((const char*)wgt + lane * (4 * 5168), 5168), 240u));
    asm volatile("bar.arrive 11, 288;" ::: "memory");
  }
  if (warp == 9) {
    sts(sb + SM_EXP + 4, min(sample_exp((const char*)xin + ((uint32_t)(first(0) + 2 * lane + (lane & 1) * IMG) * (CH * 2u) + lane % 6 * 64), CH / 2 + 16), 138u));
    asm volatile("bar.arrive 12, 192;\nbar.arrive 13, 288;" ::: "memory");
  }
  if (warp < 8) {
    const int t0 = warp * gridDim.x + blockIdx.x;
    if (P.second || t0 >= NFILT) { cluster_wait(); asm volatile("bar.sync 11, 288;" ::: "memory"); }
    if (!P.second) {
      bool ok = true;
      if (t0 >= NFILT) made(P.ready, 1);
#pragma unroll 1
      for (int t = t0; t < NFILT; t += 8 * gridDim.x) ok = filter_task(wgt, P.U, t, lane, sb + SM_EXP, t == t0, t + 8 * gridDim.x >= NFILT, P.ready) && ok;
      if (!ok) atomicOr(P.ready, 1u << 31);
      made(P.ready, 1024);
      if (warp == 0) SPAN(1);
    }
  }
  if (warp == 8) {
    uint32_t v; asm volatile("ld.volatile.global.u32 %0, [%1];" : "=r"(v) : "l"(P.ready) : "memory");
    if (v < P.nfirst) __nanosleep(100);
  }
  if (threadIdx.x == 352) {
    for (int i = 0; i < 2 * NUST; i++) { mbar_init(sb + BAR_U + 16 * i, 1); mbar_init(sb + BAR_U + 16 * i + 8, cm + 1); }
    for (int i = 0; i < 6; i++) { mbar_init(sb + BAR_TFULL + 8 * i, 5); mbar_init(sb + BAR_TEMPTY + 8 * i, 8); }
    sts(sb + SM_FLAG, 0u); sts(sb + SM_EXP + 8, 0u);
    asm volatile("fence.mbarrier_init.release.cluster;" ::: "memory");
    for (int i = 0; i < 2 * NUST; i++) mbar_expect_tx(sb + BAR_U + 16 * i, UTILE);
  }
  const uint32_t rbar = __shfl_sync(0xffffffffu, sb + BAR_RFULL + (warp & 3) * 32, 0), rbuf = sb + SM_R + (warp & 3) * (NRS * RSLOT),
                 ralt = sb + SM_T + 8 * TUNIT + (warp & 3) * (2 * RSLOT);
  if (warp >= 12) {
    if (lane == 0) {
      for (int i = 0; i < 4; i++) mbar_init(rbar + 8 * i, 1);
      asm volatile("fence.mbarrier_init.release.cluster;" ::: "memory");
    }
    __syncwarp();
    if (!P.second) __nanosleep(RAW_DELAY);
    const int o = first(0);
#pragma unroll
    for (int i = 0; i < 4; i++)
      if (i < 2 || (START4 && nit)) fetch(nit ? &xmap8 : &xmap4, nit ? RSLOT : RSLOT / 2, (i < 2 ? rbuf : ralt) + (i & 1) * RSLOT, rbar + 8 * i, 0, (o & 511) - 1 + (warp & 3) * 16 + i * 4, (o >> 9) - 1, POL_NORMAL);
#pragma unroll
    for (int i = 0; i < PF_FIRST; i++) {
      const int x = (o & 511) + (warp & 3) * 16 + (lane & 15), y = (o >> 9) - 1 + 2 * (i & 3) + (lane >> 4);
      if ((uint32_t)y < IMG) asm volatile("prefetch.global.L2 [%0];" ::"l"((const char*)xin + ((uint32_t)(y * IMG + x) * (CH * 2u) + (i >> 2) * 128)));
    }
  }
  __syncwarp();
  if (warp == 11) asm volatile("barrier.cluster.arrive.relaxed.aligned;" ::: "memory");
  if (warp == 8 || warp > 10) cluster_wait();
  if (warp > 10) asm volatile("bar.sync 12, 192;" ::: "memory");
  if (warp < 8) asm volatile("bar.sync 13, 288;" ::: "memory");
  uint2 ex;
  lds(ex, sb + SM_EXP);
  const uint32_t kin = h2((139 - ex.y) << 7);

  if (warp >= 12) {
    asm volatile("setmaxnreg.dec.sync.aligned.u32 %0;" ::"n"(REG_T));
    const int wi = warp - 12;
    const uint32_t tb = __shfl_sync(0xffffffffu, sb + SM_T + ((lane >> 1) & 3) * TCOL + (wi * 16 + (lane >> 3)) * 16 + (lane & 1) * 8, lane);
    const uint32_t src = rbuf + __shfl_sync(0xffffffffu, lane * 8, lane);
    const uint32_t nb = __shfl_sync(0xffffffffu, lane & blockIdx.y, lane);
    static_assert(NRS == 2, "box q of a chunk lies in slot q & 1 and is followed by the box after the next");
    int o = origin(0), x = (o & 511) - 1 + wi * 16, y = (o >> 9) - 1;
    uint32_t m = 0;
    auto chunk = [&](auto fill, auto start, int i, uint32_t c, int xn, int yn) {
      constexpr int NR = fill.value ? 4 : 8;
      const CUtensorMap* const map = fill.value ? &xmap4 : &xmap8;
      const uint4 un = P.un[6 * fill.value + c];
      const bool turn = c == 5, half = fill.value || (turn && i + 1 == nit);
      const CUtensorMap* const map1 = half ? &xmap4 : &xmap8;
      const int c1 = turn ? 0 : c * 32 + 32, x1 = turn ? xn : x, y1 = turn ? yn : y;
      const uint32_t n1 = half ? RSLOT / 2 : RSLOT;
#pragma unroll
      for (int q = 0; q < 4; q++) {
        const bool alt = start.value && q >= 2;
        const uint32_t sl = (q & 1) * RSLOT, rb = rbar + (alt ? q : q & 1) * 8;
        uint2 d[8];
        mbar_wait_sleep(rb, !alt && q >> 1);
#pragma unroll
        for (int r = 0; r < NR; r++) lds(d[r], src + (alt ? ralt - rbuf : 0) + sl + r * RROW);
#pragma unroll
        for (int r = 0; r < NR; r++) scale(d[r], kin, m);
        if (start.value) {
          if (q < 2) { arrive_elect(rb); fetch(map, RSLOT | (m & nb), rbuf + sl, rb, 32, x + 4 * q, y, POL_FIRST); }
        } else if (q < 2) fetch(map, NR * RROW | (m & nb), rbuf + sl, rb, c * 32, x + 8 + 4 * q, y, c & 1 ? POL_FIRST : POL_NORMAL);
        else if (!fill.value || !turn) {
          fetch(map1, n1 | (m & nb), rbuf + sl, rb, c1, x1 + 4 * q - 8, y1, c & 1 ? POL_NORMAL : POL_FIRST);
        }
#pragma unroll
        for (int r = 0; r < NR; r++) tohalf(d[r]);
        if (q == 0 && !start.value && (!fill.value || c < 3)) mbar_wait_sleep(sb + BAR_TEMPTY + 8 * c, (i & 1) ^ (c < 2));
        if (q == 0 && wi == 0) TRACE(2, tn);
        const uint32_t t = tb + 64 * q;
        if (fill.value) planes4(d, t + un.x, t + un.y);
        else planes8(d, t + un.x, t + un.y, t + un.z, t + un.w);
      }
      if (turn) {
        if (out_of_range(m)) asm volatile("red.shared.or.b32 [%0], %1;" ::"r"(sb + SM_FLAG), "r"(1u << i) : "memory");
        m = 0; x = xn; y = yn;
      }
      asm volatile("fence.proxy.async.shared::cta;" ::: "memory");
      __syncwarp();
      arrive_elect(sb + BAR_TFULL + 8 * c);
    };
    typedef std::integral_constant<int, 0> no;
    typedef std::integral_constant<int, 1> yes;
    if (START4 && nit) chunk(no(), yes(), 0, 0, 0, 0);
#pragma unroll 1
    for (int i = 0; i < nit; i++) {
      o = origin(i + 1);
#pragma unroll 1
      for (uint32_t c = START4 && i == 0; c < 6; c++) chunk(no(), no(), i, c, (o & 511) - 1 + wi * 16, (o >> 9) - 1);
    }
#pragma unroll 1
    for (uint32_t c = 0; c < 6; c++) chunk(yes(), no(), nit, c, 0, 0);
    cluster_sync();
  } else if (warp >= 8) {
    asm volatile("setmaxnreg.dec.sync.aligned.u32 24;");
    if (warp < 10) {
      const uint32_t g = warp - 8, s0 = rank ^ (5 * g & cm);
      const uint32_t ring = sb + SM_U + g * (NUST * UTILE), ub = sb + BAR_U + g * (NUST * 16);
#define PFA 5
#define PFB 10
#define PFC 0
      auto ahead = [&](int i, uint32_t sl, int r) {
        const int o = origin(i), y = o >> 9, nr = i < nit ? 6 : 2;
        const int yy = r < nr ? y + r : -2;
        if ((r & 1) == g && r < nr)
          asm volatile("{\n.reg .pred p;\nelect.sync _|p, 0xffffffff;\n@p cp.async.bulk.prefetch.tensor.3d.L2.global [%0, {%1,%2,%3}];\n}" ::"l"(&xmap1), "r"(sl * 64), "r"((o & 511) - 1), "r"(yy) : "memory");
        if ((r & 1) != g && ((r == 0 && rank == 0) || (r + 1 == nr && rank == cm)))
          asm volatile("{\n.reg .pred p;\nelect.sync _|p, 0xffffffff;\n@p cp.async.bulk.prefetch.tensor.3d.L2.global [%0, {%1,%2,%3}];\n}" ::"l"(&xmap1), "r"(sl * 64), "r"((o & 511) - 1), "r"(r ? yy + 1 : yy - 1) : "memory");
      };
      if (warp == 8) {
        uint32_t v, i = 0;
        do { asm volatile("ld.acquire.gpu.global.u32 %0, [%1];" : "=r"(v) : "l"(P.ready) : "memory"); if (++i > 5000000u) __trap(); } while ((v & 1023) < P.nfirst);
        SPAN(2);
        asm volatile("bar.arrive 7, 64;" ::: "memory");
      }
      asm volatile("bar.sync 9, 64;" ::: "memory");
      asm volatile("fence.proxy.async.global;" ::: "memory");
      uint32_t ph = 1;
#pragma unroll 1
      for (int i = 0; i <= nit; i++) {
        const uint8_t* from = P.U + g * UWG + (i < nit ? 0 : NROUND * NUST * UTILE);
#pragma unroll 1
        for (uint32_t t = 0; t < (i < nit ? NROUND : NFROUND); t++, ph ^= 1, from += NUST * UTILE) {
          if (i == 0 && t == 36 / NUST) asm volatile("bar.sync 8, 96;\nfence.proxy.async.global;" ::: "memory");
#pragma unroll 1
          for (uint32_t s = s0; s < NUST; s += cm + 1) {
            mbar_wait(ub + 16 * s + 8, ph);
            asm volatile(
                "{\n.reg .pred p;\n"
                "elect.sync _|p, 0xffffffff;\n"
                "@p cp.async.bulk.shared::cluster.global.mbarrier::complete_tx::bytes.multicast::cluster [%0], [%1], %2, [%4], %3;\n}"
                ::"r"(ring + s * UTILE), "l"(from + s * UTILE), "n"(UTILE), "h"((uint16_t)((2u << cm) - 1)), "r"(ub + 16 * s) : "memory");
            if (s == s0) {
              if (PF1 && i + t == 0) {
#pragma unroll 1
                for (int r = 0; r < 6; r++) ahead(0, 1, r);
              }
              if (PFC < 5 ? t - PFC < 6 : i < nit && t - PFC < 6) ahead(PFC < 5 ? i : i + 1, 2, t - PFC);
              if (PFC >= 5 && i == 0 && t - 1 < 6) ahead(0, 2, t - 1);
              if (i < nit && t - PFA < 6) ahead(i + 1, 0, t - PFA);
              if (i < nit && t - PFB < 6) ahead(i + 1, 1, t - PFB);
            }
            if (i < nit || t + PFU < NFROUND) {
              const uint8_t* a = from + ((int)s + (t + PFU < NROUND || i + 1 >= nit ? PFU : PFU - NROUND) * NUST) * UTILE;
              if (((cl + t) & PFU_MASK) == 0 && !P.second)
                asm volatile("{\n.reg .pred p;\nelect.sync _|p, 0xffffffff;\n@p cp.async.bulk.prefetch.L2.global [%0], %1;\n}" ::"l"(a), "n"(UTILE) : "memory");
            }
          }
        }
      }
    } else if (warp == 10) {
      uint32_t v, i = 0;
      do { asm volatile("ld.acquire.gpu.global.u32 %0, [%1];" : "=r"(v) : "l"(P.ready) : "memory"); if (++i > 5000000u) __trap(); } while (((v >> 10) & 1023) < P.nfirst);
      if (v >> 31) asm volatile("red.shared.or.b32 [%0], %1;" ::"r"(sb + SM_FLAG), "r"(0xFFFFu) : "memory");
      __syncwarp();
      asm volatile("bar.arrive 8, 96;" ::: "memory");
      asm volatile("bar.sync 7, 64;" ::: "memory");
      if (P.second && lane == 0 && ((atomicAdd(P.ready, 1 << 20) >> 20) & 1023) == gridDim.x - 1) *P.ready = 0;
      asm volatile("griddepcontrol.launch_dependents;");
    } else {
      const uint32_t tb = sb + SM_T + ((lane >> 2) & 3) * TCOL + (64 + (lane >> 4)) * 16 + (lane & 3) * 4;
      uint32_t iph = 0;
#pragma unroll 1
      for (int i = 0; i <= nit; i++, iph ^= 1) {
        const int o = origin(i), x = (o & 511) + 63 + (lane >> 4), y = (o >> 9) - 1, nr = i < nit ? 8 : 4;
        const char* p = (const char*)xin + (uint32_t)(o + 63 + (lane >> 4)) * (CH * 2u) + (lane & 15) * 4;
        uint32_t m = 0;
#pragma unroll 1
        for (uint32_t c = 0; c < 6; c++, p += 64) {
          uint32_t d[8];
#pragma unroll
          for (int r = 0; r < 8; r++) {
            d[r] = 0;
            if (x < IMG && (uint32_t)(y + r) < IMG && r < nr) asm volatile("ld.global.nc.u32 %0, [%1];" : "=r"(d[r]) : "l"(p + (r - 1) * ROWB));
          }
#pragma unroll
          for (int r = 0; r < 8; r++) { scale(d[r], kin, m); tohalf(d[r]); }
          if (i < nit || c < 3) mbar_wait_sleep(sb + BAR_TEMPTY + 8 * c, iph ^ (c < 2));
          if (i < nit) planes8(d, tb + unit(UN_P, c) * TUNIT, tb + unit(UN_Q, c) * TUNIT, tb + unit(UN_R, c) * TUNIT, tb + unit(UN_S, c) * TUNIT);
          else planes4(d, tb + unit(UN_FP, c) * TUNIT, tb + unit(UN_FQ, c) * TUNIT);
          if (c == 5 && (m & 0x78007800u)) asm volatile("red.shared.or.b32 [%0], %1;" ::"r"(sb + SM_FLAG), "r"(1u << i) : "memory");
          asm volatile("fence.proxy.async.shared::cta;" ::: "memory");
          __syncwarp();
          arrive_elect(sb + BAR_TFULL + 8 * c);
        }
      }
      if (P.second == 2) asm volatile("griddepcontrol.wait;" ::: "memory");
    }
    __syncwarp();
    cluster_sync();
  } else {
    const uint32_t ek = ex.x + ex.y - 119;
    asm volatile("setmaxnreg.inc.sync.aligned.u32 %0;" ::"n"(REG_M));
    const int wg = warp >> 2;
    Ctx C;
    C.sb = sb; C.wg = wg;
    C.b0 = sb + BAR_U + wg * (NUST * 16);
    C.bd = desc(BLO + (((sb + SM_U + wg * (NUST * UTILE)) & 0x3FFFF) >> 4), BHI);
    C.ad = desc(ALO + (((sb + SM_T + wg * TWG) & 0x3FFFF) >> 4), AHI);
    C.me = __shfl_sync(0xffffffffu, threadIdx.x & 127, lane); C.tx = __shfl_sync(0xffffffffu, lane < NUST ? UTILE : 0, lane);
    asm volatile("mapa.shared::cluster.u32 %0, %1, %2;" : "=r"(C.ra) : "r"(C.b0 + 16 * lane + 8), "r"((lane ^ 5 * wg) & cm));
    C.ok = 0;
    const uint32_t t16 = __shfl_sync(0xffffffffu, (warp & 3) * 512 + lane * 16, lane);
    C.one = (t16 & 511) == 0;
    C.xs = sb + SM_T + wg * TWG + t16;
    C.xr = sb + SM_T + (wg ^ 1) * TWG + t16;
    C.xb = sb + SM_T + (wg ^ 1) * TWG; C.t16 = t16;
    C.k = h2(ek << 7); C.sg = wg ? H_1 : H_N1;
    C.yes = C.sb != gridDim.x;
    const int drow = wg ? -2 * ROWB : 2 * ROWB;
    const char* const ob = (const char*)out + (FAKE128 ? (uint32_t)(((warp & 3) * 16 + ((lane >> 2) & 6)) * CH + (lane & 7) * 8) * 2u : (uint32_t)(((warp & 3) * 16 + (lane >> 2)) * CH + (lane & 3) * 8) * 2u);
    C.o = ob;
#pragma unroll
    for (int i = 0; i < 12; i++) C.w[i] = 0;

    Acc A0, A1, A2, A3;
#pragma unroll
    for (int j = 0; j < 48; j++) { A0[j] = 0; A1[j] = 0; A2[j] = 0; A3[j] = 0; }
#define G(W, LEAD, N0, FILL, U) group<W, LEAD, N0, FILL>(A0, A1, A2, A3, C, C.ad + (U) * (TUNIT >> 4))
    uint32_t ph = 0;
#pragma unroll 1
    for (int item = 0;; item++) {
      C.on = item != 0;
      if (P.second && item == PAUSE_AT) {
        const int wait = (5 - nit) * PAUSE_A - PAUSE_B;
        uint32_t c0, c;
        asm volatile("mov.u32 %0, %%clock;" : "=r"(c0));
        do { __nanosleep(500); asm volatile("mov.u32 %0, %%clock;" : "=r"(c)); } while ((int)(c - c0) < wait);
      }
      C.ad += item & blockIdx.y; C.bd += item & blockIdx.y;
      mbar_wait(sb + BAR_TFULL, ph);
      G(0, 1, 0, 0, unit(UN_P, 0));
      if (warp == 0 && item == 0) SPAN(10);
      G(1, 1, 6, 0, unit(UN_Q, 0));
      mbar_wait(sb + BAR_TFULL + 8, ph);
      G(0, 0, 12, 0, unit(UN_P, 1)); G(1, 0, 18, 0, unit(UN_Q, 1));
      mbar_wait(sb + BAR_TFULL + 16, ph);
      G(0, 0, 24, 0, unit(UN_P, 2)); G(1, 0, 30, 0, unit(UN_Q, 2));
      C.o -= 2 * drow;
      if (item == nit) break;
      G(2, 1, 36, 0, unit(UN_R, 0)); G(2, 0, 42, 0, unit(UN_R, 1)); G(2, 0, 48, 0, unit(UN_R, 2));
      mbar_wait(sb + BAR_TFULL + 24, ph);
      G(2, 0, 54, 0, unit(UN_R, 3)); G(0, 0, 60, 0, unit(UN_P, 3)); G(1, 0, 66, 0, unit(UN_Q, 3));
      mbar_wait(sb + BAR_TFULL + 32, ph);
      G(2, 0, 72, 0, unit(UN_R, 4)); G(0, 0, 78, 0, unit(UN_P, 4)); G(1, 0, 84, 0, unit(UN_Q, 4));
      mbar_wait(sb + BAR_TFULL + 40, ph);
      G(2, 0, 90, 0, unit(UN_R, 5)); G(0, 0, 96, 0, unit(UN_P, 5)); G(1, 0, 102, 0, unit(UN_Q, 5));
      ph ^= 1;
      C.o = ob + (uint32_t)(origin(item) + (2 + wg) * IMG) * (CH * 2u);
      G(3, 1, 108, 0, unit(UN_S, 0)); G(3, 0, 114, 0, unit(UN_S, 1)); G(3, 0, 120, 0, unit(UN_S, 2));
      G(3, 0, 126, 0, unit(UN_S, 3)); G(3, 0, 132, 0, unit(UN_S, 4)); G(3, 0, 138, 0, unit(UN_S, 5));
      C.o += drow;
      if (warp == 0) SPAN(4 + item);
    }
    mbar_wait(sb + BAR_TFULL + 24, ph);
    G(0, 0, 36, 1, unit(UN_FP, 3));
    mbar_wait(sb + BAR_TFULL + 32, ph);
    G(0, 0, 42, 1, unit(UN_FP, 4));
    mbar_wait(sb + BAR_TFULL + 40, ph);
    G(0, 0, 48, 1, unit(UN_FP, 5));
    G(1, 0, 54, 1, unit(UN_FQ, 3)); G(1, 0, 60, 1, unit(UN_FQ, 4)); G(1, 0, 66, 1, unit(UN_FQ, 5));
#undef G
    wg_wait<0>();
    if (warp == 0) SPAN(9);
    uint32_t redo;
    asm volatile("ld.shared.u32 %0, [%1];" : "=r"(redo) : "r"(sb + SM_FLAG) : "memory");
    if (cl < P.nfill) {
      C.o = ob + (uint32_t)(origin(nit) + wg * IMG) * (CH * 2u);
      join<0, 48>(A1, A0);
      put<0, 2>(A1, C); put<1, 2>(A1, C); put<2, 2>(A1, C); put<3, 2>(A1, C); put<4, 2>(A1, C); put<5, 2>(A1, C);
      put<6, 2>(A1, C); put<7, 2>(A1, C); put<8, 2>(A1, C); put<9, 2>(A1, C); put<10, 2>(A1, C); put<11, 2>(A1, C);
    }
    if (warp == 4) SPAN(3);
    sts(sb + SM_EXP + 8, 1u);
    if (ek - 1 > 253) redo = 0xFFFF;
    if (redo) {
      asm volatile("bar.sync 5, 256;" ::: "memory");
      const int k = threadIdx.x;
#pragma unroll 1
      for (int i = 0; i < nit + (cl < P.nfill); i++) {
        if (!((redo >> i) & 1) || k >= CH) continue;
        const int o = origin(i);
#pragma unroll 1
        for (int t = 0; t < (i < nit ? 48 : 16); t++) {
          const int y = (o >> 9) + (t >> 3), x = (o & 511) + (t & 7) * 8;
          float acc[8];
#pragma unroll
          for (int j = 0; j < 8; j++) acc[j] = 0.f;
#pragma unroll 1
          for (int rs = 0; rs < 9; rs++) {
            const int yy = y + rs / 3 - 1, xx = x + rs % 3 - 1;
            if ((uint32_t)yy >= IMG) continue;
#pragma unroll 1
            for (int c = 0; c < CH; c += 2) {
              const float w0 = __bfloat162float(wgt[(rs * CH + c) * CH + k]), w1 = __bfloat162float(wgt[(rs * CH + c + 1) * CH + k]);
#pragma unroll
              for (int j = 0; j < 8; j++) {
                if ((uint32_t)(xx + j) < IMG) {
                  const uint32_t v = __ldg(reinterpret_cast<const uint32_t*>(xin + (yy * IMG + xx + j) * CH + c));
                  acc[j] = fmaf(__uint_as_float(v & 0xFFFF0000u), w1, fmaf(__uint_as_float(v << 16), w0, acc[j]));
                }
              }
            }
          }
#pragma unroll
          for (int j = 0; j < 8; j++) out[(y * IMG + x + j) * CH + k] = __float2bfloat16(acc[j]);
        }
      }
    }
    __syncwarp();
    cluster_sync();
  }
}

typedef CUresult (*EncFn)(CUtensorMap*, CUtensorMapDataType, cuuint32_t, void*, const cuuint64_t*, const cuuint64_t*,
                          const cuuint32_t*, const cuuint32_t*, CUtensorMapInterleave, CUtensorMapSwizzle,
                          CUtensorMapL2promotion, CUtensorMapFloatOOBfill);

}

extern "C" void kernel_launch(void* const* d_in, const int* in_sizes, int n_in, void* d_out, int out_size) {
  const __nv_bfloat16* x = (const __nv_bfloat16*)d_in[0];
  const __nv_bfloat16* w = (const __nv_bfloat16*)d_in[1];
  __nv_bfloat16* out = (__nv_bfloat16*)d_out;

  static EncFn enc = nullptr;
  static void *U = nullptr, *ready = nullptr;
  if (!enc) {
    cudaGetSymbolAddress(&U, g_U);
    cudaGetSymbolAddress(&ready, g_ready);
    void* fn = nullptr; cudaDriverEntryPointQueryResult st;
    cudaGetDriverEntryPoint("cuTensorMapEncodeTiled", &fn, cudaEnableDefault, &st);
    enc = (EncFn)fn;
    cudaFuncSetAttribute(wino_main, cudaFuncAttributeMaxDynamicSharedMemorySize, SMEM_BYTES);
  }
  CUtensorMap xmap[3];
  for (int i = 0; i < 3; i++) {
    cuuint64_t dims[3] = {CH, IMG, IMG};
    cuuint64_t str[2] = {CH * 2, (cuuint64_t)ROWB};
    cuuint32_t box[3] = {i < 2 ? 32u : 64u, i < 2 ? 4u : 66u, i == 0 ? 8u : i == 1 ? 4u : 1u};
    cuuint32_t es[3] = {1, 1, 1};
    enc(&xmap[i], CU_TENSOR_MAP_DATA_TYPE_BFLOAT16, 3, (void*)x, dims, str, box, es, CU_TENSOR_MAP_INTERLEAVE_NONE,
        CU_TENSOR_MAP_SWIZZLE_NONE, CU_TENSOR_MAP_L2_PROMOTION_L2_128B, CU_TENSOR_MAP_FLOAT_OOB_FILL_NONE);
  }
  cudaLaunchConfig_t cfg = {};
  cudaLaunchAttribute attr[2];
  cfg.blockDim = dim3(NTHREADS);
  cfg.dynamicSmemBytes = SMEM_BYTES;
  cfg.stream = cudaStreamPerThread;
  attr[0].id = cudaLaunchAttributeClusterDimension;
  attr[0].val.clusterDim.x = 1 << LGA; attr[0].val.clusterDim.y = 1; attr[0].val.clusterDim.z = 1;
  attr[1].id = cudaLaunchAttributeProgrammaticStreamSerialization;
  attr[1].val.programmaticStreamSerializationAllowed = 1;
  cfg.attrs = attr;
  static int nca = 0, ncb = 0;
  if (!nca) {
    int n = 0, n2 = 0;
    cfg.numAttrs = 1;
    cfg.gridDim = dim3(128);
    cudaOccupancyMaxActiveClusters(&n, wino_main, &cfg);
    attr[0].val.clusterDim.x = 2;
    cudaOccupancyMaxActiveClusters(&n2, wino_main, &cfg);
    attr[0].val.clusterDim.x = 1 << LGA;
    nca = n < 1 ? 1 : n > 16 ? 16 : n;
    ncb = n2 - (nca << LGA) / 2;
  }
  cfg.numAttrs = 1;
  cfg.gridDim = dim3(nca << LGA);
  Params P = {(uint8_t*)U, (uint32_t*)ready, LGA, 5, 1, 5 * nca, 5, nca, 0, 0, nca << LGA};
  for (int c = 0; c < 6; c++) {
    P.un[c] = make_uint4(unit(UN_P, c) * TUNIT, unit(UN_Q, c) * TUNIT, unit(UN_R, c) * TUNIT, unit(UN_S, c) * TUNIT);
    P.un[6 + c] = make_uint4(unit(UN_FP, c) * TUNIT, unit(UN_FQ, c) * TUNIT, 0, 0);
  }
  cudaLaunchKernelEx(&cfg, wino_main, xmap[0], xmap[1], xmap[2], x, w, out, P);
  const int nf = 4 * (16 - nca), nb = nf == 0 ? 1 : ncb < nf ? nf : ncb > 5 * nf ? 5 * nf : ncb;
  attr[0].val.clusterDim.x = 2;
  cfg.numAttrs = 2;
  cfg.gridDim = dim3(2 * nb);
  cudaStreamCaptureStatus cap = cudaStreamCaptureStatusNone;
  cudaStreamIsCapturing(cfg.stream, &cap);
  P.lg = 1; P.ufirst = 1; P.ustep = nb; P.nunit = 5 * nf; P.nfill = nf; P.s0 = nca; P.second = cap == cudaStreamCaptureStatusActive ? 1 : 2;
  cudaLaunchKernelEx(&cfg, wino_main, xmap[0], xmap[1], xmap[2], x, w, out, P);
}
```

```cpp
#include <cuda_runtime.h>
#include <cuda.h>
#include <cuda_bf16.h>
#include <cuda_fp16.h>
#include <stdint.h>
#include <type_traits>

namespace {

constexpr int IMG = 512;
constexpr int CH = 192;
constexpr int ROWB = IMG * CH * 2;
constexpr int TCOL = 66 * 16;
constexpr int TUNIT = 4 * TCOL;
constexpr int TWG = 12 * TUNIT;
constexpr int RROW = 4 * 64;
constexpr int RSLOT = 8 * RROW;
#define X_NUST 9
constexpr int NRS = X_NUST == 9 ? 2 : 3;
constexpr int UTILE = 192 * 32;
constexpr int NUST = X_NUST;
constexpr int NROUND = 144 / NUST, NFROUND = 72 / NUST;
constexpr int UWG = (NROUND + NFROUND) * NUST * UTILE;
constexpr int SM_U = 0;
constexpr int SM_R = SM_U + 2 * NUST * UTILE;
constexpr int SM_T = 131072 - 1024;
constexpr int SM_BAR = SM_T + 2 * TWG;
static_assert(SM_R + 4 * NRS * RSLOT <= SM_T, "smem");
constexpr int SMEM_BYTES = SM_BAR + 256 + 32 * NUST + 16;
constexpr int NTHREADS = 512;
constexpr int LGA = 3;
constexpr uint32_t BAR_TFULL = SM_BAR, BAR_TEMPTY = SM_BAR + 48, SM_FLAG = SM_BAR + 96, SM_ORG = SM_BAR + 100, SM_EXP = SM_BAR + 256 + 32 * NUST, BAR_RFULL = SM_BAR + 128,
                   BAR_U = SM_BAR + 256;
static_assert(SMEM_BYTES <= 232448 && SM_R % 128 == 0, "smem");
#define UBITS 8
#define PF_START 500
#define PFU 3
#define NQ 6
#define RAW_DELAY 300
#define PF_FIRST 0
#define NSW 4
#define HOLD2 0
#define PF1 0
#define START4 0
#define PAUSE_A 28000
#define PAUSE_B 10000
#define FAKE128 0
#define PFU_MASK 7
#define PFW 0
#define PFT 1
#define PFP 0
#define PFP_SHARE 12
#define PAUSE_AT 2
#define PFW_N 4
#define PFX_E 0
#define PFX_L 13
#define PFX_T0 32
#define PFX_T1 32
#define PFX_D 9
#define POL_PF POL_SAME
#define POL_EVEN POL_SAME
#define REL2 1
#define RELT 0
#define SKEW0 66
#define SKEW1 71
#define REG_M 224
#define REG_T 40

__host__ __device__ constexpr int group_of(int q, int c) {
  return q == 0 ? (c < 3 ? 2 * c : 3 * c + 1) : q == 1 ? (c < 3 ? 2 * c + 1 : 3 * c + 2) : q == 2 ? (c < 3 ? 6 + c : 3 * c) : q == 3 ? 18 + c
       : q == 4 ? 24 + (c < 3 ? 2 * c : 3 + c) : 24 + (c < 3 ? 2 * c + 1 : 6 + c);
}
constexpr uint32_t UN_P = 0x141820, UN_Q = 0x252941, UN_R = 0x030A53, UN_S = 0xA98B76, UN_FP = 0xA53820, UN_FQ = 0xB76941;
__host__ __device__ constexpr uint32_t unit(uint32_t tab, int c) { return (tab >> (4 * c)) & 15; }

__device__ __align__(1024) uint8_t g_U[2 * UWG];
__device__ uint32_t g_ready;
#define SPAN(k)
#define TRACE(row, i)

__device__ __forceinline__ void cluster_wait() { asm volatile("barrier.cluster.wait.acquire.aligned;" ::: "memory"); }
__device__ __forceinline__ uint32_t sample_exp(const char* p, uint32_t stride) {
  uint32_t m = 0;
  uint4 v[4];
#pragma unroll
  for (int i = 0; i < 4; i++)
    asm volatile("ld.global.nc.v4.u32 {%0,%1,%2,%3}, [%4];" : "=r"(v[i].x), "=r"(v[i].y), "=r"(v[i].z), "=r"(v[i].w) : "l"(p + i * stride));
  cluster_wait();
#pragma unroll
  for (int i = 0; i < 4; i++)
    m = __vmaxu2(__vmaxu2(m, __vmaxu2(v[i].x & 0x7FFF7FFFu, v[i].y & 0x7FFF7FFFu)), __vmaxu2(v[i].z & 0x7FFF7FFFu, v[i].w & 0x7FFF7FFFu));
  m = __reduce_max_sync(0xffffffffu, max(m & 0xFFFFu, m >> 16)) >> 7;
  return m ? m : 120;
}

constexpr int NFILT = 2 * 6 * 24 * 3;
__device__ __forceinline__ void made(uint32_t* ready, uint32_t n) {
  asm volatile("fence.proxy.async.global;\nbar.sync 10, 256;" ::: "memory");
  if (threadIdx.x == 0) asm volatile("red.release.gpu.global.add.u32 [%0], %1;" ::"l"(ready), "r"(n) : "memory");
  __syncwarp();
}
__device__ __forceinline__ bool filter_task(const __nv_bfloat16* __restrict__ w, uint8_t* U, int t, int lane, uint32_t ew, bool first, bool last, uint32_t* ready) {
  const int wg = t & 1, blk = (t >> 1) % 6, co = (t / 12) % 24, s = t / (12 * 24);
  const int k = blk * 32 + ((lane >> 1) & 3) * 8 + (lane >> 3) * 2 + (lane & 1);
  const unsigned short* wp = reinterpret_cast<const unsigned short*>(w) + ((wg * 6 + s) * CH + co * 8) * CH + k;
  const int dr = wg ? -3 * CH * CH : 3 * CH * CH;
  uint32_t g[3][8];
#pragma unroll
  for (int r = 0; r < 3; r++)
#pragma unroll
    for (int i = 0; i < 8; i++) asm volatile("ld.global.nc.u16 %0, [%1];" : "=r"(g[r][i]) : "l"(wp + r * dr + i * CH));
  const int chunk = co >> 2;
  uint8_t* const u = U + wg * UWG + (3 * ((co >> 1) & 1) + s) * UTILE + (blk * 4 + (lane >> 3)) * 256 + (co & 1) * 128 + (lane & 7) * 16;
  if (first) { cluster_wait(); asm volatile("bar.sync 11, 288;" ::: "memory"); }
  asm volatile("ld.shared.u32 %0, [%0];" : "+r"(ew)::"memory");
  const float su = __uint_as_float((249 - ew) << 23), low = __uint_as_float(15u << 23);
  const float na = (wg ? 128.f / 90.f : 1.f / 1.40625f) * low, sg = wg ? -1.f : 1.f;
  float v[5][8], m = 0.f;
#pragma unroll
  for (int i = 0; i < 8; i++) {
    const float a = __uint_as_float(g[0][i] << 16) * su, b = __uint_as_float(g[1][i] << 16) * su, c = __uint_as_float(g[2][i] << 16) * su;
    asm("{\n.reg .f32 t;\nmax.NaN.f32 t, %1, %2;\nmax.NaN.f32 %0, %0, %3;\nmax.NaN.f32 %0, %0, t;\n}" : "+f"(m) : "f"(fabsf(a)), "f"(fabsf(b)), "f"(fabsf(c)));
    const float e = fmaf(0.25f, c, a) * na, o = b * (0.5f * na), d = fmaf(a + c, sg, b);
    v[0][i] = e + o; v[1][i] = (e - o) * sg; v[2][i] = d * (low / -4.5f); v[3][i] = a * (-sg * low); v[4][i] = d * (0.5f * low);
  }
#pragma unroll
  for (int q = 0; q < 5; q++) {
    uint32_t pk[4];
#pragma unroll
    for (int i = 0; i < 4; i++) {
      asm("cvt.rn.bf16x2.f32 %0, %1, %2;" : "=r"(pk[i]) : "f"(v[q][2 * i + 1]), "f"(v[q][2 * i]));
      pk[i] += (pk[i] & 0x7FFF7FFFu) * 7;
    }
    *reinterpret_cast<uint4*>(u + 6 * group_of(q, chunk) * UTILE) = make_uint4(pk[0], pk[1], pk[2], pk[3]);
    if (q == 3) *reinterpret_cast<uint4*>(u + 6 * group_of(5, chunk) * UTILE) = make_uint4(pk[0], pk[1], pk[2], pk[3]);
    if (q == 1 && last) made(ready, 1);
  }
  return m < 0.1875f;
}

__device__ __forceinline__ uint32_t smem_u32(const void* p) { return (uint32_t)__cvta_generic_to_shared(p); }
__device__ __forceinline__ void mbar_init(uint32_t bar, uint32_t cnt) {
  asm volatile("mbarrier.init.shared::cta.b64 [%0], %1;" ::"r"(bar), "r"(cnt));
}
__device__ __forceinline__ void mbar_expect_tx(uint32_t bar, uint32_t bytes) {
  asm volatile("mbarrier.arrive.expect_tx.shared::cta.b64 _, [%0], %1;" ::"r"(bar), "r"(bytes) : "memory");
}
__device__ __forceinline__ void mbar_wait(uint32_t bar, uint32_t parity) {
  asm volatile(
      "{\n.reg .pred p;\n"
      "WAIT_%=:\n"
      "mbarrier.try_wait.parity.shared::cta.b64 p, [%0], %1;\n"
      "@p bra DONE_%=;\n"
      "bra WAIT_%=;\n"
      "DONE_%=:\n}" ::"r"(bar), "r"(parity) : "memory");
}
__device__ __forceinline__ uint32_t mbar_try(uint32_t bar, uint32_t parity) {
  uint32_t ok;
  asm volatile(
      "{\n.reg .pred p;\n"
      "mbarrier.test_wait.parity.shared::cta.b64 p, [%1], %2;\n"
      "selp.u32 %0, 1, 0, p;\n}" : "=r"(ok) : "r"(bar), "r"(parity) : "memory");
  return ok;
}
__device__ __forceinline__ void mbar_wait_sleep(uint32_t bar, uint32_t parity) {
  asm volatile(
      "{\n.reg .pred p;\n"
      "WAIT_%=:\n"
      "mbarrier.try_wait.parity.shared::cta.b64 p, [%0], %1, 20000;\n"
      "@p bra DONE_%=;\n"
      "bra WAIT_%=;\n"
      "DONE_%=:\n}" ::"r"(bar), "r"(parity) : "memory");
}
#undef mbar_wait
#undef mbar_wait_sleep
__device__ __forceinline__ void arrive_elect(uint32_t bar) {
  asm volatile(
      "{\n.reg .pred p;\n"
      "elect.sync _|p, 0xffffffff;\n"
      "@p mbarrier.arrive.shared::cta.b64 _, [%0];\n}" ::"r"(bar) : "memory");
}
__device__ __forceinline__ void cluster_sync() {
  asm volatile("barrier.cluster.arrive.relaxed.aligned;\nbarrier.cluster.wait.aligned;" ::: "memory");
}
__device__ __forceinline__ void wg_fence() { asm volatile("wgmma.fence.sync.aligned;" ::: "memory"); }
__device__ __forceinline__ void wg_commit() { asm volatile("wgmma.commit_group.sync.aligned;" ::: "memory"); }
template <int N> __device__ __forceinline__ void wg_wait() { asm volatile("wgmma.wait_group.sync.aligned %0;" ::"n"(N) : "memory"); }
template <int LEAD>
__device__ __forceinline__ void wgmma192(uint32_t (&d)[48], uint64_t adesc, uint64_t bdesc, uint32_t acc) {
  asm volatile(
      "{\n.reg .pred p;\n"
      "setp.ne.b32 p, %50, 0;\n"
      "wgmma.mma_async.sync.aligned.m64n192k16.f16.f16.f16 "
      "{%0,%1,%2,%3,%4,%5,%6,%7,%8,%9,%10,%11,%12,%13,%14,%15,%16,%17,%18,%19,%20,%21,%22,%23,%24,%25,%26,%27,%28,%29,%30,%31,%32,%33,%34,%35,%36,%37,%38,%39,%40,%41,%42,%43,%44,%45,%46,%47}, %48, %49, p, 1, 1, 0, 0;\n}\n"
      : "+r"(d[0]),"+r"(d[1]),"+r"(d[2]),"+r"(d[3]),"+r"(d[4]),"+r"(d[5]),"+r"(d[6]),"+r"(d[7]),"+r"(d[8]),"+r"(d[9]),"+r"(d[10]),"+r"(d[11]),"+r"(d[12]),"+r"(d[13]),"+r"(d[14]),"+r"(d[15]),"+r"(d[16]),"+r"(d[17]),"+r"(d[18]),"+r"(d[19]),"+r"(d[20]),"+r"(d[21]),"+r"(d[22]),"+r"(d[23]),"+r"(d[24]),"+r"(d[25]),"+r"(d[26]),"+r"(d[27]),"+r"(d[28]),"+r"(d[29]),"+r"(d[30]),"+r"(d[31]),"+r"(d[32]),"+r"(d[33]),"+r"(d[34]),"+r"(d[35]),"+r"(d[36]),"+r"(d[37]),"+r"(d[38]),"+r"(d[39]),"+r"(d[40]),"+r"(d[41]),"+r"(d[42]),"+r"(d[43]),"+r"(d[44]),"+r"(d[45]),"+r"(d[46]),"+r"(d[47])
      : "l"(adesc), "l"(bdesc), "r"(LEAD ? acc : 1u));
}

__device__ __forceinline__ void sts(uint32_t addr, uint32_t v) { asm volatile("st.shared.u32 [%0], %1;" ::"r"(addr), "r"(v) : "memory"); }
__device__ __forceinline__ void sts(uint32_t addr, uint2 v) { asm volatile("st.shared.v2.u32 [%0], {%1,%2};" ::"r"(addr), "r"(v.x), "r"(v.y) : "memory"); }
__device__ __forceinline__ void lds(uint32_t& v, uint32_t addr) { asm volatile("ld.shared.u32 %0, [%1];" : "=r"(v) : "r"(addr) : "memory"); }
__device__ __forceinline__ void lds(uint2& v, uint32_t addr) { asm volatile("ld.shared.v2.u32 {%0,%1}, [%2];" : "=r"(v.x), "=r"(v.y) : "r"(addr) : "memory"); }
__host__ __device__ constexpr uint32_t h2(uint32_t h) { return h | (h << 16); }
constexpr uint32_t H_2 = h2(0x4000), H_1_2 = h2(0x3800), H_1_4 = h2(0x3400), H_1_8 = h2(0x3000), H_1_16 = h2(0x2C00), H_1_32 = h2(0x2800),
                   H_N4 = h2(0xC400), H_N2 = h2(0xC000), H_N1_2 = h2(0xB800), H_N1_4 = h2(0xB400), H_N17_4 = h2(0xC440), H_1 = h2(0x3C00), H_N1 = h2(0xBC00);
__device__ __forceinline__ uint32_t hfma(uint32_t a, uint32_t b, uint32_t c) {
  uint32_t r; asm("fma.rn.f16x2 %0, %1, %2, %3;" : "=r"(r) : "r"(a), "r"(b), "r"(c)); return r;
}
__device__ __forceinline__ uint32_t hadd(uint32_t a, uint32_t b) { uint32_t r; asm("add.rn.f16x2 %0, %1, %2;" : "=r"(r) : "r"(a), "r"(b)); return r; }
__device__ __forceinline__ uint32_t hsub(uint32_t a, uint32_t b) { uint32_t r; asm("sub.rn.f16x2 %0, %1, %2;" : "=r"(r) : "r"(a), "r"(b)); return r; }
__device__ __forceinline__ uint2 hfma(uint2 a, uint32_t b, uint2 c) { return make_uint2(hfma(a.x, b, c.x), hfma(a.y, b, c.y)); }
__device__ __forceinline__ uint2 hadd(uint2 a, uint2 b) { return make_uint2(hadd(a.x, b.x), hadd(a.y, b.y)); }
__device__ __forceinline__ uint2 hsub(uint2 a, uint2 b) { return make_uint2(hsub(a.x, b.x), hsub(a.y, b.y)); }
__device__ __forceinline__ uint32_t bmul(uint32_t x, uint32_t k) { uint32_t z; asm("mul.rn.bf16x2 %0, %1, %2;" : "=r"(z) : "r"(x), "r"(k)); return z; }
__device__ __forceinline__ void scale(uint32_t& x, uint32_t k, uint32_t& m) { x = bmul(x, k); m |= x; }
__device__ __forceinline__ void scale(uint2& x, uint32_t k, uint32_t& m) {
  x.x = bmul(x.x, k); x.y = bmul(x.y, k);
  asm("lop3.b32 %0, %0, %1, %2, 0xFE;" : "+r"(m) : "r"(x.x), "r"(x.y));
}
__device__ __forceinline__ void tohalf(uint32_t& z) { z = (z & 0x7FFF7FFFu) * 7 + z; }
__device__ __forceinline__ void tohalf(uint2& z) { tohalf(z.x); tohalf(z.y); }
__device__ __forceinline__ bool out_of_range(uint32_t m) {
  m = __reduce_or_sync(0xffffffffu, m & 0x7FFF7FFFu);
  return (m & 0x78007800u) || (m && !(m & 0x06000600u));
}

#define TMASK 0xFFFFFFFFu
__device__ __forceinline__ void stt(uint32_t a, uint32_t v) { sts(a, v & TMASK); }
__device__ __forceinline__ void stt(uint32_t a, uint2 v) { sts(a, make_uint2(v.x & TMASK, v.y & TMASK)); }
template <typename V>
__device__ __forceinline__ void planes8(V (&d)[8], uint32_t dp, uint32_t dq, uint32_t dr, uint32_t ds) {
  const V ec = hfma(d[4], H_N17_4, hadd(d[6], d[2])), oc = hfma(d[3], H_N17_4, hadd(d[5], d[1]));
  stt(dr, hadd(ec, oc)); stt(dr + TWG, hsub(ec, oc));
#pragma unroll
  for (int k = 0; k < 6; k++) d[k] = hsub(d[k + 2], d[k]);
  const V ea = hfma(d[2], H_N4, d[4]), oa = hfma(d[1], H_N4, d[3]);
  stt(dp, hfma(oa, H_1_2, ea)); stt(dq, hfma(oa, H_N1_2, ea));
  stt(ds, hfma(hfma(d[0], H_N4, d[2]), H_N1_4, ea)); stt(ds + TWG, hfma(oa, H_N1_4, hfma(d[3], H_N4, d[5])));
  const V eb = hfma(d[2], H_N1_4, d[4]), ob = hfma(d[1], H_N1_4, d[3]);
  stt(dp + TWG, hfma(ob, H_2, eb)); stt(dq + TWG, hfma(ob, H_N2, eb));
}
template <typename V>
__device__ __forceinline__ void planes4(V (&d)[8], uint32_t dp, uint32_t dq) {
  stt(dp, hadd(d[2], d[1])); stt(dp + TWG, hsub(d[2], d[1]));
  stt(dq, hsub(d[2], d[0])); stt(dq + TWG, hsub(d[3], d[1]));
}

__device__ __forceinline__ void planes8(uint32_t (&d)[8], uint32_t (&o)[8]) {
  const uint32_t ec = hfma(d[4], H_N17_4, hadd(d[6], d[2])), oc = hfma(d[3], H_N17_4, hadd(d[5], d[1]));
#pragma unroll
  for (int k = 0; k < 6; k++) d[k] = hsub(d[k + 2], d[k]);
  const uint32_t ea = hfma(d[2], H_N4, d[4]), oa = hfma(d[1], H_N4, d[3]), e0 = hfma(d[0], H_N4, d[2]), o5 = hfma(d[3], H_N4, d[5]);
  const uint32_t eb = hfma(d[2], H_N1_4, d[4]), ob = hfma(d[1], H_N1_4, d[3]);
  o[0] = hfma(oa, H_1_2, ea); o[1] = hfma(oa, H_N1_2, ea); o[2] = hadd(ec, oc); o[3] = hfma(e0, H_N1_4, ea);
  o[4] = hfma(ob, H_2, eb); o[5] = hfma(ob, H_N2, eb); o[6] = hsub(ec, oc); o[7] = hfma(oa, H_N1_4, o5);
}
__device__ __forceinline__ void planes4(uint32_t (&d)[8], uint32_t (&o)[8]) {
  o[0] = hadd(d[2], d[1]); o[1] = hsub(d[2], d[0]); o[4] = hsub(d[2], d[1]); o[5] = hsub(d[3], d[1]);
}

constexpr uint32_t BHI = 256 >> 4, BLO = (128 >> 4) << 16, AHI = 128 >> 4, ALO = (TCOL >> 4) << 16;
__device__ __forceinline__ uint64_t desc(uint32_t lo, uint32_t hi) { uint64_t d; asm("mov.b64 %0, {%1,%2};" : "=l"(d) : "r"(lo), "r"(hi)); return d; }

typedef uint32_t Acc[48];
struct Ctx {
  uint32_t sb;
  uint64_t ad, bd;
  uint32_t b0;
  uint32_t me, ra, tx;
  uint32_t ok;
  bool one;
  uint32_t wg, xs, xr, xb, t16;
  uint32_t w[12];
  uint32_t k, sg;
  const char* o;
  bool on, yes;
};
__device__ __forceinline__ void arrive(uint32_t bar, bool on) {
  asm volatile("{\n.reg .pred p;\nsetp.ne.b32 p, %1, 0;\n@p mbarrier.arrive.shared::cta.b64 _, [%0];\n}" ::"r"(bar), "r"((uint32_t)on) : "memory");
}
template <int S>
__device__ __forceinline__ void release(Ctx& C, uint32_t me, uint32_t tx) {
  asm volatile(
      "{\n.reg .pred p;\n"
      "setp.ne.b32 p, %1, 0;\n"
      "@p mbarrier.arrive.expect_tx.shared::cta.b64 _, [%0], %1;\n}" ::"r"(C.b0 + 16 * S), "r"(tx) : "memory");
  asm volatile(
      "{\n.reg .pred p;\n"
      "setp.eq.b32 p, %0, %2;\n"
      "@p mbarrier.arrive.shared::cluster.b64 _, [%1];\n}" ::"r"(me), "r"(C.ra), "n"(S) : "memory");
}
template <int SYNC, int ID0, int ID1>
__device__ __forceinline__ void bar(uint32_t wg) {
  if (SYNC) asm volatile("{\n.reg .pred p;\nsetp.ne.b32 p, %0, 0;\n@!p bar.sync %1, 256;\n@p bar.sync %2, 256;\n}" ::"r"(wg), "n"(ID0), "n"(ID1) : "memory");
  else asm volatile("{\n.reg .pred p;\nsetp.ne.b32 p, %0, 0;\n@!p bar.arrive %1, 256;\n@p bar.arrive %2, 256;\n}" ::"r"(wg), "n"(ID0), "n"(ID1) : "memory");
}
__device__ __forceinline__ void sent(Ctx& C) { bar<0, 1, 2>(C.wg); }
__device__ __forceinline__ void await_sent(Ctx& C) { bar<1, 2, 1>(C.wg); }
__device__ __forceinline__ void sent2(Ctx& C) { bar<0, 10, 11>(C.wg); }
__device__ __forceinline__ void await_sent2(Ctx& C) { bar<1, 11, 10>(C.wg); }
__device__ __forceinline__ void await_taken(Ctx& C) { bar<1, 3, 4>(C.wg); }
__device__ __forceinline__ void taken(Ctx& C, uint32_t x) { if ((x & blockIdx.y) == 0) bar<0, 4, 3>(C.wg); }

#define BEHIND 1
#define LAND 0
__device__ __forceinline__ void landed(uint32_t x) { if (LAND && (x & blockIdx.y)) __trap(); }
__host__ __device__ constexpr int xoff(int u, int h) { return u * TUNIT + h * 2048; }
template <int B, int OF>
__device__ __forceinline__ void send(const Acc& A, uint32_t addr) {
  asm volatile("st.shared.v4.u32 [%4 + %5], {%0,%1,%2,%3};" ::"r"(A[4 * B]), "r"(A[4 * B + 1]), "r"(A[4 * B + 2]), "r"(A[4 * B + 3]), "r"(addr), "n"(OF) : "memory");
}
template <int B, int OF>
__device__ __forceinline__ void recv(Acc& A, uint32_t addr, bool on) {
  asm volatile("{\n.reg .pred p;\nsetp.ne.b32 p, %6, 0;\n@p ld.shared.v4.u32 {%0,%1,%2,%3}, [%4 + %5];\n}"
               : "+r"(A[4 * B]), "+r"(A[4 * B + 1]), "+r"(A[4 * B + 2]), "+r"(A[4 * B + 3]) : "r"(addr), "n"(OF), "r"((uint32_t)on) : "memory");
}
template <int OF>
__device__ __forceinline__ void fetch4(uint32_t* w, uint32_t addr) {
  asm volatile("ld.shared.v4.u32 {%0,%1,%2,%3}, [%4 + %5];" : "=r"(w[0]), "=r"(w[1]), "=r"(w[2]), "=r"(w[3]) : "r"(addr), "n"(OF) : "memory");
}
template <int I, int N>
__device__ __forceinline__ void add_to(Acc& A, const uint32_t* w, uint32_t sg) {
#pragma unroll
  for (int j = 0; j < N; j++) asm volatile("fma.rn.f16x2 %0, %1, %2, %0;" : "+r"(A[I + j]) : "r"(w[j]), "r"(sg));
}
template <int I, int N>
__device__ __forceinline__ void join(Acc& A, const Acc& B) {
#pragma unroll
  for (int j = I; j < I + N; j++) asm volatile("add.rn.f16x2 %0, %0, %1;" : "+r"(A[j]) : "r"(B[j]));
}
template <int B, int OF>
__device__ __forceinline__ void split(Acc& A, const Acc& Bb, uint32_t* w, uint32_t addr) {
#pragma unroll
  for (int j = 0; j < 4; j++)
    asm volatile("sub.rn.f16x2 %0, %1, %2;\nadd.rn.f16x2 %1, %1, %2;" : "=&r"(w[j]), "+r"(A[4 * B + j]) : "r"(Bb[4 * B + j]));
  asm volatile("st.shared.v4.u32 [%4 + %5], {%0,%1,%2,%3};" ::"r"(w[0]), "r"(w[1]), "r"(w[2]), "r"(w[3]), "r"(addr), "n"(OF) : "memory");
}
#define KORD 1
__host__ __device__ constexpr int pj(int k) { return KORD ? 2 * (k >> 2) + (k & 1) : k >> 1; }
__host__ __device__ constexpr int ph_(int k) { return KORD ? (k >> 1) & 1 : k & 1; }
template <int K>
__device__ __forceinline__ void rows(const Acc& P, Acc& Q, Acc& R, uint32_t* w) {
#pragma unroll
  for (int i = 0; i < 4; i++) {
    const int j = 8 * pj(K) + 2 * i + ph_(K);
    asm volatile(
        "{\n.reg .b32 a, b;\n"
        "fma.rn.f16x2 a, %1, %4, %2;\n fma.rn.f16x2 b, %1, %5, %2;\n fma.rn.f16x2 %1, %1, %6, %2;\n"
        "fma.rn.f16x2 %0, %3, %7, a;\n fma.rn.f16x2 %2, %3, %8, b;\n add.rn.f16x2 %1, %1, %3;\n}"
        : "=r"(w[i]), "+r"(Q[j]), "+r"(R[j]) : "r"(P[j]), "r"(H_1_8), "r"(H_1_2), "r"(H_1_32), "r"(H_1_4), "r"(H_1_16));
  }
}
__device__ __forceinline__ uint32_t tobf(uint32_t h, uint32_t k) {
  uint32_t o;
  asm volatile("{\n.reg .b16 l, u;\n.reg .f32 a, b;\n.reg .b32 t;\nmov.b32 {l, u}, %1;\ncvt.f32.f16 a, l;\ncvt.f32.f16 b, u;\n"
               "cvt.rn.bf16x2.f32 t, b, a;\nmul.rn.bf16x2 %0, t, %2;\n}" : "=r"(o) : "r"(h), "r"(k));
  return o;
}
template <int K>
__device__ __forceinline__ void stg4(const char* o, const uint32_t* r) {
#define STQ ".cs"
  asm volatile("st.global" STQ ".v4.u32 [%4 + %5], {%0,%1,%2,%3};" ::"r"(r[0]), "r"(r[1]), "r"(r[2]), "r"(r[3]), "l"(o), "n"(FAKE128 ? ph_(K) * 8 * CH * 2 + (K & 1) * CH * 2 + (K >> 2) * 128 : ph_(K) * 8 * CH * 2 + pj(K) * 64) : "memory");
}
template <int K, int NOW = 1>
__device__ __forceinline__ void put(const Acc& A, Ctx& C) {
  uint32_t* w = C.w + (NOW == 2 ? 4 * (K & 1) : 8);
#pragma unroll
  for (int i = 0; i < 4; i++) w[i] = tobf(A[8 * pj(K) + 2 * i + ph_(K)], C.k);
  if (NOW) stg4<K>(C.o, w);
}

#define OUT_R 0x252949290ull
#define OUT_S 0x084210842108421ull
#define OUT_M 0x151551540ull
#define OUT_F 0x281015555ull
#define E0_AT 6
#define E1_AT 27
#define LATE 0
#define AW_SIDE 0
#define ST_EARLY 0
__host__ __device__ constexpr int below(uint64_t m, int n) { return __builtin_popcountll(m & ((1ull << n) - 1)); }
static_assert(below(OUT_R, 36) == 12 && below(OUT_S, 60) == 12 && below(OUT_M, 35) == 12 && below(OUT_F, 36) == 12, "pieces");
static_assert(!(OUT_R & 15) && !(OUT_M & 0xC03F) && !(OUT_M & (OUT_M << 1)) && below(OUT_M, 8) <= 1 && below(OUT_M, 12) <= 4 && below(OUT_M, 24) <= 8 && below(OUT_M, 28) <= 9 && !(OUT_F & 0x7E000000) && E0_AT >= 6 && E1_AT >= 27, "order");

__host__ __device__ constexpr int r_out(int n) { return n >= 96 && n < 100 ? n - 96 : n == 124 || n == 125 ? n - 120 : -1; }
__host__ __device__ constexpr int d_out(int n) { return n >= 108 && n < 112 ? n - 108 : n == 122 || n == 123 ? n - 118 : -1; }
__host__ __device__ constexpr int r_in(int n) { return n >= 101 && n < 109 ? n - 101 : n == 130 || n == 131 ? n - 122 : n == 134 || n == 135 ? n - 124 : -1; }
__host__ __device__ constexpr int d_in(int n) { return n >= 112 && n < 120 ? n - 112 : n == 128 || n == 129 ? n - 120 : n == 132 || n == 133 ? n - 122 : -1; }
constexpr uint32_t XU_R = 0x750354, XU_D = 0x425421, XU_F = 0x984210;
template <int N, int FILL>
__device__ __forceinline__ void early(Acc& P, Acc& Q, Acc& R, Acc& S, Ctx& C) {
  if constexpr (ST_EARLY) {
    if constexpr (FILL && N > 36) { if constexpr ((OUT_F >> (N - 37)) & 1) { if (C.on) stg4<below(OUT_F, N - 37)>(C.o, C.w + 8); } }
    if constexpr (!FILL && N > 0 && N < 36) { if constexpr ((OUT_R >> (N - 1)) & 1) { if (C.on) stg4<below(OUT_R, N - 1)>(C.o, C.w + 8); } }
    if constexpr (!FILL && N > 36 && N < 97) { if constexpr ((OUT_S >> (N - 37)) & 1) { if (C.on) stg4<below(OUT_S, N - 37)>(C.o, C.w + 8); } }
    if constexpr (!FILL && N > 109) { if constexpr ((OUT_M >> (N - 110)) & 1) stg4<below(OUT_M, N - 110)>(C.o, C.w + 8); }
  }
  if constexpr (FILL) {
    constexpr int I = N - 61;
    if constexpr (I == 0) await_sent(C);
    if constexpr (I >= 0 && I < 6) { fetch4<xoff(unit(XU_F, I), 0)>(C.w, C.xr); fetch4<xoff(unit(XU_F, I), 1)>(C.w + 4, C.xr); }
  } else {
    if constexpr (N == 101 || N == 116) await_sent(C);
    if constexpr (N == 112 || N == 128) await_sent2(C);
    if constexpr (r_in(N) >= 0) {
      constexpr int B = r_in(N);
      fetch4<xoff(unit(XU_R, B / 2), B & 1)>(C.w + 4, C.xr);
    }
    if constexpr (d_in(N) >= 0) {
      constexpr bool dep = BEHIND && ((OUT_M >> (N - 109)) & 1);
      recv<d_in(N), xoff(unit(XU_D, d_in(N) / 2), d_in(N) & 1)>(Q, dep ? C.xb + (C.t16 | (C.w[3] & blockIdx.y)) : C.xr, C.yes);
    }
  }
}
template <int N, int FILL>
__device__ __forceinline__ void side(Acc& P, Acc& Q, Acc& R, Acc& S, Ctx& C) {
  const uint32_t te = C.sb + BAR_TEMPTY;
  if constexpr (FILL) {
    constexpr int I = N - 36, X = N - 54;
    if constexpr ((OUT_F >> I) & 1) { if (C.on) put<below(OUT_F, I), !ST_EARLY>(S, C); }
    if constexpr (X >= 0 && X < 6) { send<2 * X, xoff(unit(XU_F, X), 0)>(P, C.xs); send<2 * X + 1, xoff(unit(XU_F, X), 1)>(P, C.xs); }
    if constexpr (X == 5) sent(C);
    if constexpr (N == SKEW0) { if (C.wg) asm volatile("bar.sync 6, 256;" ::: "memory"); }
    if constexpr (N == SKEW1) { if (!C.wg) asm volatile("bar.arrive 6, 256;" ::: "memory"); }
    if constexpr (N >= 61 && N < 67) { if (C.yes) add_to<8 * (N - 61), 8>(P, C.w, C.sg); }
  } else if constexpr (N < 36) {
    if constexpr (N == 0) arrive(te + 16, C.one);
    if constexpr (N < 4) { if (C.on) join<12 * N, 12>(S, Q); }
    if constexpr ((OUT_R >> N) & 1) { if (C.on) put<below(OUT_R, N), !ST_EARLY>(R, C); }
    if constexpr (N == 30) arrive(te + 24, C.one);
  } else if constexpr (N < 96) {
    if constexpr ((OUT_S >> (N - 36)) & 1) { if (C.on) put<below(OUT_S, N - 36), !ST_EARLY>(S, C); }
    if constexpr (N == 48) arrive(te + 32, C.one);
    if constexpr (N == 72) arrive(te + 40, C.one);
  } else {
    constexpr int I = N - 108;
    if constexpr (I > 0) {
      if constexpr ((OUT_M >> (I - 1)) & 1) {
        if (C.yes) {
#pragma unroll
          for (int i = 0; i < 4; i++) C.w[8 + i] = tobf(C.w[i], C.k);
        }
        if (!ST_EARLY) stg4<below(OUT_M, I - 1)>(C.o, C.w + 8);
      }
    }
    if constexpr (I >= 0) {
      if constexpr ((OUT_M >> I) & 1) { if (C.yes) rows<below(OUT_M, I)>(P, Q, R, C.w); }
    }
    if constexpr (N == 110 || N == 122) await_taken(C);
    if constexpr (r_out(N) >= 0) {
      constexpr int X = r_out(N);
      send<2 * X, xoff(unit(XU_R, X), 0)>(R, C.xs); send<2 * X + 1, xoff(unit(XU_R, X), 1)>(R, C.xs);
    }
    if constexpr (r_in(N) >= 0) {
      if (C.yes) {
        add_to<4 * r_in(N), 4>(R, C.w + 4, C.sg);
      }
    }
    if constexpr (d_out(N) >= 0) {
      constexpr int X = d_out(N);
      if (C.yes) { split<2 * X, xoff(unit(XU_D, X), 0)>(P, Q, C.w + 4, C.xs); split<2 * X + 1, xoff(unit(XU_D, X), 1)>(P, Q, C.w, C.xs); }
    }
    if constexpr (N == 99 || N == 111) sent(C);
    if constexpr (N == 109 || N == 125) sent2(C);
    if constexpr (N == 108) taken(C, R[31]);
    if constexpr (N == 120) taken(C, Q[11] | Q[15] | Q[19] | Q[23] | Q[27] | Q[31]);
    if constexpr (I == E0_AT) arrive(te, C.one && ((Q[3] | Q[7]) & blockIdx.y) == 0);
    if constexpr (I == E1_AT) arrive(te + 8, C.one && ((R[47] | Q[35] | Q[39] | Q[43] | Q[47]) & blockIdx.y) == 0);
  }
}
template <int W, int LEAD, int N0, int FILL, int J = 0>
__device__ __forceinline__ void group(Acc& P, Acc& Q, Acc& R, Acc& S, Ctx& C, uint64_t a) {
  constexpr int N = N0 + J;
  if (!C.ok) mbar_wait(C.b0 + 16 * (N % NUST), (N / NUST) & 1);
  wg_fence();
  wgmma192<LEAD && J == 0>(W == 0 ? P : W == 1 ? Q : W == 2 ? R : S, a + (((J / 3) * 2 * TCOL + (J % 3) * 16) >> 4), C.bd + (N % NUST) * (UTILE >> 4), blockIdx.y);
  wg_commit();
  C.ok = mbar_try(C.b0 + 16 * ((N + 1) % NUST), ((N + 1) / NUST) & 1);
  if constexpr (LATE && N > 0) side<N - 1, FILL && N != 36>(P, Q, R, S, C);
  early<N, FILL>(P, Q, R, S, C);
  wg_wait<1>();
  release<(N + NUST - 1) % NUST>(C, N || C.on ? C.me : 0, N || C.on ? C.tx : 0);
  if constexpr (!LATE) side<N, FILL>(P, Q, R, S, C);
  if constexpr (J < 5) group<W, LEAD, N0, FILL, J + 1>(P, Q, R, S, C, a);
}

__device__ __forceinline__ void fetch(const CUtensorMap* map, uint32_t bytes, uint32_t dst, uint32_t bar, int c, int x, int y, uint64_t pol) {
  asm volatile("{\n.reg .pred p;\nelect.sync _|p, 0xffffffff;\n"
               "@p mbarrier.arrive.expect_tx.shared::cta.b64 _, [%2], %6;\n"
               "@p cp.async.bulk.tensor.3d.shared::cluster.global.mbarrier::complete_tx::bytes.L2::cache_hint [%0], [%1, {%3,%4,%5}], [%2], %7;\n}"
               ::"r"(dst), "l"(map), "r"(bar), "r"(c), "r"(x), "r"(y), "r"(bytes), "l"(pol) : "memory");
}
constexpr uint64_t POL_NORMAL = 0x16F0000000000000ull, POL_FIRST = 0x12F0000000000000ull, POL_SAME = 0x10F0000000000000ull;

struct Params { uint8_t* U; uint32_t* ready; int lg, ufirst, ustep, nunit, umax, nfill, s0, second, nfirst; uint4 un[12]; };

__global__ void __launch_bounds__(NTHREADS, 1) wino_main(const __grid_constant__ CUtensorMap xmap8, const __grid_constant__ CUtensorMap xmap4,
                                                         const __grid_constant__ CUtensorMap xmap1,
                                                         const __nv_bfloat16* __restrict__ xin, const __nv_bfloat16* __restrict__ wgt,
                                                         __nv_bfloat16* __restrict__ out, const Params P) {
  extern __shared__ __align__(1024) uint8_t smem[];
  { const uint32_t l = threadIdx.x * gridDim.x + blockIdx.x; if (l < 9 * CH * CH * 2 / 128) asm volatile("prefetch.global.L2 [%0];" ::"l"((const char*)wgt + l * 128u)); }
  const uint32_t sb = smem_u32(smem);
  const int warp = __shfl_sync(0xffffffffu, threadIdx.x >> 5, 0), lane = threadIdx.x & 31;
  const uint32_t cm = (1u << P.lg) - 1, rank = blockIdx.x & cm;
  const int cl = blockIdx.x >> P.lg;
  if (P.nfill == 0) {
    asm volatile("griddepcontrol.wait;" ::: "memory");
    *P.ready = 0;
    return;
  }
  const int nit = min(P.umax, (P.nunit - cl * P.ufirst + P.ustep - 1) / P.ustep), fu = cl % P.nfill;
  auto first = [&](int i) {
    const int u = cl * P.ufirst + i * P.ustep, q = (u * (205 << (P.lg - 1))) >> 12;
    const int st = P.s0 + (i < nit ? q : fu >> (3 - P.lg));
    const int y = i < nit ? ((u - q * (40 >> P.lg)) * 6 << P.lg) + 6 * rank : 240 + ((fu & ((8 >> P.lg) - 1)) * 2 << P.lg) + 2 * rank;
    return (st & 7) * 64 + ((st >> 3) * 256 + y) * IMG;
  };

  auto origin = [&](int i) { int o; asm volatile("ld.shared.u32 %0, [%1];" : "=r"(o) : "r"(sb + SM_ORG + 4 * i)); return o; };
  if (warp == 11 && lane < 7) sts(sb + SM_ORG + 4 * lane, (uint32_t)first(min(lane, nit)));

  const bool C_yes = sb != gridDim.x;
  if (warp == 0) SPAN(0);
  if (warp != 11) asm volatile("barrier.cluster.arrive.relaxed.aligned;" ::: "memory");
  if (warp == 10) {
    sts(sb + SM_EXP, min(sample_exp((const char*)wgt + lane * (4 * 5168), 5168), 240u));
    asm volatile("bar.arrive 11, 288;" ::: "memory");
  }
  if (warp == 9) {
    sts(sb + SM_EXP + 4, min(sample_exp((const char*)xin + ((uint32_t)(first(0) + 2 * lane + (lane & 1) * IMG) * (CH * 2u) + lane % 6 * 64), CH / 2 + 16), 138u));
    asm volatile("bar.arrive 12, 192;\nbar.arrive 13, 288;" ::: "memory");
  }
  if (warp < 8) {
    const int t0 = warp * gridDim.x + blockIdx.x;
    if (P.second || t0 >= NFILT) { cluster_wait(); asm volatile("bar.sync 11, 288;" ::: "memory"); }
    if (!P.second) {
      bool ok = true;
      if (t0 >= NFILT) made(P.ready, 1);
#pragma unroll 1
      for (int t = t0; t < NFILT; t += 8 * gridDim.x) ok = filter_task(wgt, P.U, t, lane, sb + SM_EXP, t == t0, t + 8 * gridDim.x >= NFILT, P.ready) && ok;
      if (!ok) atomicOr(P.ready, 1u << 31);
      made(P.ready, 1024);
      if (warp == 0) SPAN(1);
    }
  }
  if (warp == 8) {
    uint32_t v; asm volatile("ld.volatile.global.u32 %0, [%1];" : "=r"(v) : "l"(P.ready) : "memory");
    if (v < P.nfirst) __nanosleep(100);
  }
  if (threadIdx.x == 352) {
    for (int i = 0; i < 2 * NUST; i++) { mbar_init(sb + BAR_U + 16 * i, 1); mbar_init(sb + BAR_U + 16 * i + 8, cm + 1); }
    for (int i = 0; i < 6; i++) { mbar_init(sb + BAR_TFULL + 8 * i, 5); mbar_init(sb + BAR_TEMPTY + 8 * i, 8); }
    sts(sb + SM_FLAG, 0u); sts(sb + SM_EXP + 8, 0u);
    asm volatile("fence.mbarrier_init.release.cluster;" ::: "memory");
    for (int i = 0; i < 2 * NUST; i++) mbar_expect_tx(sb + BAR_U + 16 * i, UTILE);
  }
  const uint32_t rbar = __shfl_sync(0xffffffffu, sb + BAR_RFULL + (warp & 3) * 32, 0), rbuf = sb + SM_R + (warp & 3) * (NRS * RSLOT),
                 ralt = sb + SM_T + 8 * TUNIT + (warp & 3) * (2 * RSLOT);
  if (warp >= 12) {
    if (lane == 0) {
      for (int i = 0; i < 4; i++) mbar_init(rbar + 8 * i, 1);
      asm volatile("fence.mbarrier_init.release.cluster;" ::: "memory");
    }
    __syncwarp();
    if (!P.second) __nanosleep(RAW_DELAY);
    const int o = first(0);
#pragma unroll
    for (int i = 0; i < 4; i++)
      if (i < 2 || (START4 && nit)) fetch(nit ? &xmap8 : &xmap4, nit ? RSLOT : RSLOT / 2, (i < 2 ? rbuf : ralt) + (i & 1) * RSLOT, rbar + 8 * i, 0, (o & 511) - 1 + (warp & 3) * 16 + i * 4, (o >> 9) - 1, POL_EVEN);
#pragma unroll
    for (int i = 0; i < PF_FIRST; i++) {
      const int x = (o & 511) + (warp & 3) * 16 + (lane & 15), y = (o >> 9) - 1 + 2 * (i & 3) + (lane >> 4);
      if ((uint32_t)y < IMG) asm volatile("prefetch.global.L2 [%0];" ::"l"((const char*)xin + ((uint32_t)(y * IMG + x) * (CH * 2u) + (i >> 2) * 128)));
    }
  }
  __syncwarp();
  if (warp == 11) asm volatile("barrier.cluster.arrive.relaxed.aligned;" ::: "memory");
  if (warp == 8 || warp > 10) cluster_wait();
  if (warp > 10) asm volatile("bar.sync 12, 192;" ::: "memory");
  if (warp < 8) asm volatile("bar.sync 13, 288;" ::: "memory");
  uint2 ex;
  lds(ex, sb + SM_EXP);
  const uint32_t kin = h2((139 - ex.y) << 7);

  if (warp >= 12) {
    asm volatile("setmaxnreg.dec.sync.aligned.u32 %0;" ::"n"(REG_T));
    const int wi = warp - 12;
    const uint32_t tb = __shfl_sync(0xffffffffu, sb + SM_T + ((lane >> 1) & 3) * TCOL + (wi * 16 + (lane >> 3)) * 16 + (lane & 1) * 8, lane);
    const uint32_t src = rbuf + __shfl_sync(0xffffffffu, lane * 8, lane);
    const uint32_t nb = __shfl_sync(0xffffffffu, lane & blockIdx.y, lane);
    static_assert(NRS == 2, "box q of a chunk lies in slot q & 1 and is followed by the box after the next");
    int o = origin(0), x = (o & 511) - 1 + wi * 16, y = (o >> 9) - 1;
    uint32_t m = 0;
    auto chunk = [&](auto fill, auto start, int i, uint32_t c, int xn, int yn) {
      constexpr int NR = fill.value ? 4 : 8;
      const CUtensorMap* const map = fill.value ? &xmap4 : &xmap8;
      const uint4 un = P.un[6 * fill.value + c];
      const bool turn = c == 5, half = fill.value || (turn && i + 1 == nit);
      const CUtensorMap* const map1 = half ? &xmap4 : &xmap8;
      const int c1 = turn ? 0 : c * 32 + 32, x1 = turn ? xn : x, y1 = turn ? yn : y;
      const uint32_t n1 = half ? RSLOT / 2 : RSLOT;
#pragma unroll
      for (int q = 0; q < 4; q++) {
        const bool alt = start.value && q >= 2;
        const uint32_t sl = (q & 1) * RSLOT, rb = rbar + (alt ? q : q & 1) * 8;
        uint2 d[8];
        mbar_wait_sleep(rb, !alt && q >> 1);
#pragma unroll
        for (int r = 0; r < NR; r++) lds(d[r], src + (alt ? ralt - rbuf : 0) + sl + r * RROW);
#pragma unroll
        for (int r = 0; r < NR; r++) scale(d[r], kin, m);
        if (start.value) {
          if (q < 2) { arrive_elect(rb); fetch(map, RSLOT | (m & nb), rbuf + sl, rb, 32, x + 4 * q, y, POL_FIRST); }
        } else if (q < 2) fetch(map, NR * RROW | (m & nb), rbuf + sl, rb, c * 32, x + 8 + 4 * q, y, c & 1 ? POL_FIRST : POL_EVEN);
        else if (!fill.value || !turn) {
          fetch(map1, n1 | (m & nb), rbuf + sl, rb, c1, x1 + 4 * q - 8, y1, c & 1 ? POL_EVEN : POL_FIRST);
        }
#pragma unroll
        for (int r = 0; r < NR; r++) tohalf(d[r]);
        if (q == 0 && !start.value && (!fill.value || c < 3)) mbar_wait_sleep(sb + BAR_TEMPTY + 8 * c, (i & 1) ^ (c < 2));
        if (q == 0 && wi == 0) TRACE(2, tn);
        const uint32_t t = tb + 64 * q;
        if (fill.value) planes4(d, t + un.x, t + un.y);
        else planes8(d, t + un.x, t + un.y, t + un.z, t + un.w);
      }
      if (turn) {
        if (out_of_range(m)) asm volatile("red.shared.or.b32 [%0], %1;" ::"r"(sb + SM_FLAG), "r"(1u << i) : "memory");
        m = 0; x = xn; y = yn;
      }
      asm volatile("fence.proxy.async.shared::cta;" ::: "memory");
      __syncwarp();
      arrive_elect(sb + BAR_TFULL + 8 * c);
    };
    typedef std::integral_constant<int, 0> no;
    typedef std::integral_constant<int, 1> yes;
    if (START4 && nit) chunk(no(), yes(), 0, 0, 0, 0);
#pragma unroll 1
    for (int i = 0; i < nit; i++) {
      o = origin(i + 1);
#pragma unroll 1
      for (uint32_t c = START4 && i == 0; c < 6; c++) chunk(no(), no(), i, c, (o & 511) - 1 + wi * 16, (o >> 9) - 1);
    }
#pragma unroll 1
    for (uint32_t c = 0; c < 6; c++) chunk(yes(), no(), nit, c, 0, 0);
    cluster_sync();
  } else if (warp >= 8) {
    asm volatile("setmaxnreg.dec.sync.aligned.u32 24;");
    if (warp < 10) {
      const uint32_t g = warp - 8, s0 = rank ^ (5 * g & cm);
      const uint32_t ring = sb + SM_U + g * (NUST * UTILE), ub = sb + BAR_U + g * (NUST * 16);
#define PFA 6
#define PFB 10
#define PFC 1
      auto ahead = [&](int i, uint32_t sl, int r) {
        const int o = origin(i), y = o >> 9, nr = i < nit ? 6 : 2;
        const int yy = r < nr ? y + r : -2;
        if ((r & 1) == g && r < nr)
          asm volatile("{\n.reg .pred p;\nelect.sync _|p, 0xffffffff;\n@p cp.async.bulk.prefetch.tensor.3d.L2.global.L2::cache_hint [%0, {%1,%2,%3}], %4;\n}" ::"l"(&xmap1), "r"(sl * 64), "r"((o & 511) - 1), "r"(yy), "l"(POL_PF) : "memory");
        if ((r & 1) != g && ((r == 0 && rank == 0) || (r + 1 == nr && rank == cm)))
          asm volatile("{\n.reg .pred p;\nelect.sync _|p, 0xffffffff;\n@p cp.async.bulk.prefetch.tensor.3d.L2.global.L2::cache_hint [%0, {%1,%2,%3}], %4;\n}" ::"l"(&xmap1), "r"(sl * 64), "r"((o & 511) - 1), "r"(r ? yy + 1 : yy - 1), "l"(POL_PF) : "memory");
      };
      if (warp == 8) {
        uint32_t v, i = 0;
        do { asm volatile("ld.acquire.gpu.global.u32 %0, [%1];" : "=r"(v) : "l"(P.ready) : "memory"); if (++i > 5000000u) __trap(); } while ((v & 1023) < P.nfirst);
        SPAN(2);
        asm volatile("bar.arrive 7, 64;" ::: "memory");
      }
      asm volatile("bar.sync 9, 64;" ::: "memory");
      asm volatile("fence.proxy.async.global;" ::: "memory");
      uint32_t ph = 1;
#pragma unroll 1
      for (int i = 0; i <= nit; i++) {
        const uint8_t* from = P.U + g * UWG + (i < nit ? 0 : NROUND * NUST * UTILE);
#pragma unroll 1
        for (uint32_t t = 0; t < (i < nit ? NROUND : NFROUND); t++, ph ^= 1, from += NUST * UTILE) {
          if (i == 0 && t == 36 / NUST) asm volatile("bar.sync 8, 96;\nfence.proxy.async.global;" ::: "memory");
#pragma unroll 1
          for (uint32_t s = s0; s < NUST; s += cm + 1) {
            mbar_wait(ub + 16 * s + 8, ph);
            asm volatile(
                "{\n.reg .pred p;\n"
                "elect.sync _|p, 0xffffffff;\n"
                "@p cp.async.bulk.shared::cluster.global.mbarrier::complete_tx::bytes.multicast::cluster [%0], [%1], %2, [%4], %3;\n}"
                ::"r"(ring + s * UTILE), "l"(from + s * UTILE), "n"(UTILE), "h"((uint16_t)((2u << cm) - 1)), "r"(ub + 16 * s) : "memory");
            if (s == s0) {
              if (t - PFC < 6) ahead(i, 2, t - PFC);
              if (i < nit && t - PFA < 6) ahead(i + 1, 0, t - PFA);
              if (i < nit && t - PFB < 6) ahead(i + 1, 1, t - PFB);
            }
            if (i < nit || t + PFU < NFROUND) {
              const uint8_t* a = from + ((int)s + (t + PFU < NROUND || i + 1 >= nit ? PFU : PFU - NROUND) * NUST) * UTILE;
              if (((cl + t) & PFU_MASK) == 0 && !P.second)
                asm volatile("{\n.reg .pred p;\nelect.sync _|p, 0xffffffff;\n@p cp.async.bulk.prefetch.L2.global [%0], %1;\n}" ::"l"(a), "n"(UTILE) : "memory");
            }
          }
        }
      }
    } else if (warp == 10) {
      uint32_t v, i = 0;
      do { asm volatile("ld.acquire.gpu.global.u32 %0, [%1];" : "=r"(v) : "l"(P.ready) : "memory"); if (++i > 5000000u) __trap(); } while (((v >> 10) & 1023) < P.nfirst);
      if (v >> 31) asm volatile("red.shared.or.b32 [%0], %1;" ::"r"(sb + SM_FLAG), "r"(0xFFFFu) : "memory");
      __syncwarp();
      asm volatile("bar.arrive 8, 96;" ::: "memory");
      asm volatile("bar.sync 7, 64;" ::: "memory");
      if (P.second && lane == 0 && ((atomicAdd(P.ready, 1 << 20) >> 20) & 1023) == gridDim.x - 1) *P.ready = 0;
      asm volatile("griddepcontrol.launch_dependents;");
    } else {
      const uint32_t tb = sb + SM_T + ((lane >> 2) & 3) * TCOL + (64 + (lane >> 4)) * 16 + (lane & 3) * 4;
      uint32_t iph = 0;
#pragma unroll 1
      for (int i = 0; i <= nit; i++, iph ^= 1) {
        const int o = origin(i), x = (o & 511) + 63 + (lane >> 4), y = (o >> 9) - 1, nr = i < nit ? 8 : 4;
        const char* p = (const char*)xin + (uint32_t)(o + 63 + (lane >> 4)) * (CH * 2u) + (lane & 15) * 4;
        uint32_t m = 0;
#pragma unroll 1
        for (uint32_t c = 0; c < 6; c++, p += 64) {
          uint32_t d[8];
#pragma unroll
          for (int r = 0; r < 8; r++) {
            d[r] = 0;
            if (x < IMG && (uint32_t)(y + r) < IMG && r < nr) asm volatile("ld.global.nc.u32 %0, [%1];" : "=r"(d[r]) : "l"(p + (r - 1) * ROWB));
          }
#pragma unroll
          for (int r = 0; r < 8; r++) { scale(d[r], kin, m); tohalf(d[r]); }
          if (i < nit || c < 3) mbar_wait_sleep(sb + BAR_TEMPTY + 8 * c, iph ^ (c < 2));
          if (i < nit) planes8(d, tb + unit(UN_P, c) * TUNIT, tb + unit(UN_Q, c) * TUNIT, tb + unit(UN_R, c) * TUNIT, tb + unit(UN_S, c) * TUNIT);
          else planes4(d, tb + unit(UN_FP, c) * TUNIT, tb + unit(UN_FQ, c) * TUNIT);
          if (c == 5 && (m & 0x78007800u)) asm volatile("red.shared.or.b32 [%0], %1;" ::"r"(sb + SM_FLAG), "r"(1u << i) : "memory");
          asm volatile("fence.proxy.async.shared::cta;" ::: "memory");
          __syncwarp();
          arrive_elect(sb + BAR_TFULL + 8 * c);
        }
      }
      if (P.second == 2) asm volatile("griddepcontrol.wait;" ::: "memory");
    }
    __syncwarp();
    cluster_sync();
  } else {
    const uint32_t ek = ex.x + ex.y - 119;
    asm volatile("setmaxnreg.inc.sync.aligned.u32 %0;" ::"n"(REG_M));
    const int wg = warp >> 2;
    Ctx C;
    C.sb = sb; C.wg = wg;
    C.b0 = sb + BAR_U + wg * (NUST * 16);
    C.bd = desc(BLO + (((sb + SM_U + wg * (NUST * UTILE)) & 0x3FFFF) >> 4), BHI);
    C.ad = desc(ALO + (((sb + SM_T + wg * TWG) & 0x3FFFF) >> 4), AHI);
    C.me = __shfl_sync(0xffffffffu, threadIdx.x & 127, lane); C.tx = __shfl_sync(0xffffffffu, (REL2 ? (threadIdx.x & 127) == RELT : lane < NUST) ? UTILE : 0, lane);
    asm volatile("mapa.shared::cluster.u32 %0, %1, %2;" : "=r"(C.ra) : "r"(C.b0 + 16 * lane + 8), "r"((lane ^ 5 * wg) & cm));
    C.ok = 0;
    const uint32_t t16 = __shfl_sync(0xffffffffu, (warp & 3) * 512 + lane * 16, lane);
    C.one = (t16 & 511) == 0;
    C.xs = sb + SM_T + wg * TWG + t16;
    C.xr = sb + SM_T + (wg ^ 1) * TWG + t16;
    C.xb = sb + SM_T + (wg ^ 1) * TWG; C.t16 = t16;
    C.k = h2(ek << 7); C.sg = wg ? H_1 : H_N1;
    C.yes = C.sb != gridDim.x;
    const int drow = wg ? -2 * ROWB : 2 * ROWB;
    const char* const ob = (const char*)out + (FAKE128 ? (uint32_t)(((warp & 3) * 16 + ((lane >> 2) & 6)) * CH + (lane & 7) * 8) * 2u : (uint32_t)(((warp & 3) * 16 + (lane >> 2)) * CH + (lane & 3) * 8) * 2u);
    C.o = ob;
#pragma unroll
    for (int i = 0; i < 12; i++) C.w[i] = 0;

    Acc A0, A1, A2, A3;
#pragma unroll
    for (int j = 0; j < 48; j++) { A0[j] = 0; A1[j] = 0; A2[j] = 0; A3[j] = 0; }
#define G(W, LEAD, N0, FILL, U) group<W, LEAD, N0, FILL>(A0, A1, A2, A3, C, C.ad + (U) * (TUNIT >> 4))
    uint32_t ph = 0;
#pragma unroll 1
    for (int item = 0;; item++) {
      C.on = item != 0;
      if (P.second && item == PAUSE_AT) {
        const int wait = (5 - nit) * PAUSE_A - PAUSE_B;
        uint32_t c0, c;
        asm volatile("mov.u32 %0, %%clock;" : "=r"(c0));
        do { __nanosleep(500); asm volatile("mov.u32 %0, %%clock;" : "=r"(c)); } while ((int)(c - c0) < wait);
      }
      C.ad += item & blockIdx.y; C.bd += item & blockIdx.y;
      mbar_wait(sb + BAR_TFULL, ph);
      G(0, 1, 0, 0, unit(UN_P, 0));
      if (warp == 0 && item == 0) SPAN(10);
      G(1, 1, 6, 0, unit(UN_Q, 0));
      mbar_wait(sb + BAR_TFULL + 8, ph);
      G(0, 0, 12, 0, unit(UN_P, 1)); G(1, 0, 18, 0, unit(UN_Q, 1));
      mbar_wait(sb + BAR_TFULL + 16, ph);
      G(0, 0, 24, 0, unit(UN_P, 2)); G(1, 0, 30, 0, unit(UN_Q, 2));
      C.o -= 2 * drow;
      if (item == nit) break;
      G(2, 1, 36, 0, unit(UN_R, 0)); G(2, 0, 42, 0, unit(UN_R, 1)); G(2, 0, 48, 0, unit(UN_R, 2));
      mbar_wait(sb + BAR_TFULL + 24, ph);
      G(2, 0, 54, 0, unit(UN_R, 3)); G(0, 0, 60, 0, unit(UN_P, 3)); G(1, 0, 66, 0, unit(UN_Q, 3));
      mbar_wait(sb + BAR_TFULL + 32, ph);
      G(2, 0, 72, 0, unit(UN_R, 4)); G(0, 0, 78, 0, unit(UN_P, 4)); G(1, 0, 84, 0, unit(UN_Q, 4));
      mbar_wait(sb + BAR_TFULL + 40, ph);
      G(2, 0, 90, 0, unit(UN_R, 5)); G(0, 0, 96, 0, unit(UN_P, 5)); G(1, 0, 102, 0, unit(UN_Q, 5));
      ph ^= 1;
      C.o = ob + (uint32_t)(origin(item) + (2 + wg) * IMG) * (CH * 2u);
      G(3, 1, 108, 0, unit(UN_S, 0)); G(3, 0, 114, 0, unit(UN_S, 1)); G(3, 0, 120, 0, unit(UN_S, 2));
      G(3, 0, 126, 0, unit(UN_S, 3)); G(3, 0, 132, 0, unit(UN_S, 4)); G(3, 0, 138, 0, unit(UN_S, 5));
      C.o += drow;
      if (warp == 0) SPAN(4 + item);
    }
    mbar_wait(sb + BAR_TFULL + 24, ph);
    G(0, 0, 36, 1, unit(UN_FP, 3));
    mbar_wait(sb + BAR_TFULL + 32, ph);
    G(0, 0, 42, 1, unit(UN_FP, 4));
    mbar_wait(sb + BAR_TFULL + 40, ph);
    G(0, 0, 48, 1, unit(UN_FP, 5));
    G(1, 0, 54, 1, unit(UN_FQ, 3)); G(1, 0, 60, 1, unit(UN_FQ, 4)); G(1, 0, 66, 1, unit(UN_FQ, 5));
#undef G
    wg_wait<0>();
    if (warp == 0) SPAN(9);
    uint32_t redo;
    asm volatile("ld.shared.u32 %0, [%1];" : "=r"(redo) : "r"(sb + SM_FLAG) : "memory");
    if (cl < P.nfill) {
      C.o = ob + (uint32_t)(origin(nit) + wg * IMG) * (CH * 2u);
      join<0, 48>(A1, A0);
      put<0, 2>(A1, C); put<1, 2>(A1, C); put<2, 2>(A1, C); put<3, 2>(A1, C); put<4, 2>(A1, C); put<5, 2>(A1, C);
      put<6, 2>(A1, C); put<7, 2>(A1, C); put<8, 2>(A1, C); put<9, 2>(A1, C); put<10, 2>(A1, C); put<11, 2>(A1, C);
    }
    if (warp == 4) SPAN(3);
    sts(sb + SM_EXP + 8, 1u);
    if (ek - 1 > 253) redo = 0xFFFF;
    if (redo) {
      asm volatile("bar.sync 5, 256;" ::: "memory");
      const int k = threadIdx.x;
#pragma unroll 1
      for (int i = 0; i < nit + (cl < P.nfill); i++) {
        if (!((redo >> i) & 1) || k >= CH) continue;
        const int o = origin(i);
#pragma unroll 1
        for (int t = 0; t < (i < nit ? 48 : 16); t++) {
          const int y = (o >> 9) + (t >> 3), x = (o & 511) + (t & 7) * 8;
          float acc[8];
#pragma unroll
          for (int j = 0; j < 8; j++) acc[j] = 0.f;
#pragma unroll 1
          for (int rs = 0; rs < 9; rs++) {
            const int yy = y + rs / 3 - 1, xx = x + rs % 3 - 1;
            if ((uint32_t)yy >= IMG) continue;
#pragma unroll 1
            for (int c = 0; c < CH; c += 2) {
              const float w0 = __bfloat162float(wgt[(rs * CH + c) * CH + k]), w1 = __bfloat162float(wgt[(rs * CH + c + 1) * CH + k]);
#pragma unroll
              for (int j = 0; j < 8; j++) {
                if ((uint32_t)(xx + j) < IMG) {
                  const uint32_t v = __ldg(reinterpret_cast<const uint32_t*>(xin + (yy * IMG + xx + j) * CH + c));
                  acc[j] = fmaf(__uint_as_float(v & 0xFFFF0000u), w1, fmaf(__uint_as_float(v << 16), w0, acc[j]));
                }
              }
            }
          }
#pragma unroll
          for (int j = 0; j < 8; j++) out[(y * IMG + x + j) * CH + k] = __float2bfloat16(acc[j]);
        }
      }
    }
    __syncwarp();
    cluster_sync();
  }
}

typedef CUresult (*EncFn)(CUtensorMap*, CUtensorMapDataType, cuuint32_t, void*, const cuuint64_t*, const cuuint64_t*,
                          const cuuint32_t*, const cuuint32_t*, CUtensorMapInterleave, CUtensorMapSwizzle,
                          CUtensorMapL2promotion, CUtensorMapFloatOOBfill);

}

extern "C" void kernel_launch(void* const* d_in, const int* in_sizes, int n_in, void* d_out, int out_size) {
  const __nv_bfloat16* x = (const __nv_bfloat16*)d_in[0];
  const __nv_bfloat16* w = (const __nv_bfloat16*)d_in[1];
  __nv_bfloat16* out = (__nv_bfloat16*)d_out;

  static EncFn enc = nullptr;
  static void *U = nullptr, *ready = nullptr;
  if (!enc) {
    cudaGetSymbolAddress(&U, g_U);
    cudaGetSymbolAddress(&ready, g_ready);
    void* fn = nullptr; cudaDriverEntryPointQueryResult st;
    cudaGetDriverEntryPoint("cuTensorMapEncodeTiled", &fn, cudaEnableDefault, &st);
    enc = (EncFn)fn;
    cudaFuncSetAttribute(wino_main, cudaFuncAttributeMaxDynamicSharedMemorySize, SMEM_BYTES);
  }
  CUtensorMap xmap[3];
  for (int i = 0; i < 3; i++) {
    cuuint64_t dims[3] = {CH, IMG, IMG};
    cuuint64_t str[2] = {CH * 2, (cuuint64_t)ROWB};
    cuuint32_t box[3] = {i < 2 ? 32u : 64u, i < 2 ? 4u : 66u, i == 0 ? 8u : i == 1 ? 4u : 1u};
    cuuint32_t es[3] = {1, 1, 1};
    enc(&xmap[i], CU_TENSOR_MAP_DATA_TYPE_BFLOAT16, 3, (void*)x, dims, str, box, es, CU_TENSOR_MAP_INTERLEAVE_NONE,
        CU_TENSOR_MAP_SWIZZLE_NONE, CU_TENSOR_MAP_L2_PROMOTION_L2_128B, CU_TENSOR_MAP_FLOAT_OOB_FILL_NONE);
  }
  cudaLaunchConfig_t cfg = {};
  cudaLaunchAttribute attr[2];
  cfg.blockDim = dim3(NTHREADS);
  cfg.dynamicSmemBytes = SMEM_BYTES;
  cfg.stream = cudaStreamPerThread;
  attr[0].id = cudaLaunchAttributeClusterDimension;
  attr[0].val.clusterDim.x = 1 << LGA; attr[0].val.clusterDim.y = 1; attr[0].val.clusterDim.z = 1;
  attr[1].id = cudaLaunchAttributeProgrammaticStreamSerialization;
  attr[1].val.programmaticStreamSerializationAllowed = 1;
  cfg.attrs = attr;
  static int nca = 0, ncb = 0;
  if (!nca) {
    int n = 0, n2 = 0;
    cfg.numAttrs = 1;
    cfg.gridDim = dim3(128);
    cudaOccupancyMaxActiveClusters(&n, wino_main, &cfg);
    attr[0].val.clusterDim.x = 2;
    cudaOccupancyMaxActiveClusters(&n2, wino_main, &cfg);
    attr[0].val.clusterDim.x = 1 << LGA;
    nca = n < 1 ? 1 : n > 16 ? 16 : n;
    ncb = n2 - (nca << LGA) / 2;
  }
  cfg.numAttrs = 1;
  cfg.gridDim = dim3(nca << LGA);
  Params P = {(uint8_t*)U, (uint32_t*)ready, LGA, 5, 1, 5 * nca, 5, nca, 0, 0, nca << LGA};
  for (int c = 0; c < 6; c++) {
    P.un[c] = make_uint4(unit(UN_P, c) * TUNIT, unit(UN_Q, c) * TUNIT, unit(UN_R, c) * TUNIT, unit(UN_S, c) * TUNIT);
    P.un[6 + c] = make_uint4(unit(UN_FP, c) * TUNIT, unit(UN_FQ, c) * TUNIT, 0, 0);
  }
  cudaLaunchKernelEx(&cfg, wino_main, xmap[0], xmap[1], xmap[2], x, w, out, P);
  const int nf = 4 * (16 - nca), nb = nf == 0 ? 1 : ncb < nf ? nf : ncb > 5 * nf ? 5 * nf : ncb;
  attr[0].val.clusterDim.x = 2;
  cfg.numAttrs = 2;
  cfg.gridDim = dim3(2 * nb);
  cudaStreamCaptureStatus cap = cudaStreamCaptureStatusNone;
  cudaStreamIsCapturing(cfg.stream, &cap);
  P.lg = 1; P.ufirst = 1; P.ustep = nb; P.nunit = 5 * nf; P.nfill = nf; P.s0 = nca; P.second = cap == cudaStreamCaptureStatusActive ? 1 : 2;
  cudaLaunchKernelEx(&cfg, wino_main, xmap[0], xmap[1], xmap[2], x, w, out, P);
}
```

```cpp
#include <cuda_runtime.h>
#include <cuda.h>
#include <cuda_bf16.h>
#include <stdint.h>
#include <type_traits>

namespace {

constexpr int IMG = 512;
constexpr int CH = 192;
constexpr int ROWB = IMG * CH * 2;
constexpr int TCOL = 66 * 16;
constexpr int TUNIT = 4 * TCOL;
constexpr int TWG = 12 * TUNIT;
constexpr int RROW = 4 * 64;
constexpr int RSLOT = 8 * RROW;
constexpr int UTILE = 192 * 32;
constexpr int NUST = 9;
constexpr int NROUND = 144 / NUST, NFROUND = 72 / NUST;
constexpr int UWG = (NROUND + NFROUND) * NUST * UTILE;
constexpr int SM_U = 0;
constexpr int SM_R = SM_U + 2 * NUST * UTILE;
constexpr int SM_T = 131072 - 1024;
constexpr int SM_BAR = SM_T + 2 * TWG;
static_assert(SM_R + 4 * 2 * RSLOT <= SM_T, "smem");
constexpr int SMEM_BYTES = SM_BAR + 256 + 32 * NUST + 16;
constexpr int NTHREADS = 512;
constexpr int LGA = 3;
constexpr uint32_t BAR_TFULL = SM_BAR, BAR_TEMPTY = SM_BAR + 48, SM_FLAG = SM_BAR + 96, SM_ORG = SM_BAR + 100, SM_EXP = SM_BAR + 256 + 32 * NUST, BAR_RFULL = SM_BAR + 128,
                   BAR_U = SM_BAR + 256;
static_assert(SMEM_BYTES <= 232448 && SM_R % 128 == 0, "smem");

__host__ __device__ constexpr int group_of(int q, int c) {
  return q == 0 ? (c < 3 ? 2 * c : 3 * c + 1) : q == 1 ? (c < 3 ? 2 * c + 1 : 3 * c + 2) : q == 2 ? (c < 3 ? 6 + c : 3 * c) : q == 3 ? 18 + c
       : q == 4 ? 24 + (c < 3 ? 2 * c : 3 + c) : 24 + (c < 3 ? 2 * c + 1 : 6 + c);
}
constexpr uint32_t UN_P = 0x141820, UN_Q = 0x252941, UN_R = 0x030A53, UN_S = 0xA98B76, UN_FP = 0xA53820, UN_FQ = 0xB76941;
__host__ __device__ constexpr uint32_t unit(uint32_t tab, int c) { return (tab >> (4 * c)) & 15; }

__device__ __align__(1024) uint8_t g_U[2 * UWG];
__device__ uint32_t g_ready;
#define TRACE(row, i)

__device__ __forceinline__ void cluster_wait() { asm volatile("barrier.cluster.wait.acquire.aligned;" ::: "memory"); }
__device__ __forceinline__ uint32_t sample_exp(const char* p, uint32_t stride) {
  uint32_t m = 0;
  uint4 v[4];
#pragma unroll
  for (int i = 0; i < 4; i++)
    asm volatile("ld.global.nc.v4.u32 {%0,%1,%2,%3}, [%4];" : "=r"(v[i].x), "=r"(v[i].y), "=r"(v[i].z), "=r"(v[i].w) : "l"(p + i * stride));
  cluster_wait();
#pragma unroll
  for (int i = 0; i < 4; i++)
    m = __vmaxu2(__vmaxu2(m, __vmaxu2(v[i].x & 0x7FFF7FFFu, v[i].y & 0x7FFF7FFFu)), __vmaxu2(v[i].z & 0x7FFF7FFFu, v[i].w & 0x7FFF7FFFu));
  return __reduce_max_sync(0xffffffffu, max(m & 0xFFFFu, m >> 16)) >> 7;
}

constexpr int NFILT = 2 * 6 * 24 * 3;
__device__ __forceinline__ void made(uint32_t* ready, uint32_t n) {
  asm volatile("fence.proxy.async.global;\nbar.sync 10, 256;" ::: "memory");
  if (threadIdx.x == 0) asm volatile("red.release.gpu.global.add.u32 [%0], %1;" ::"l"(ready), "r"(n) : "memory");
  __syncwarp();
}
__device__ __forceinline__ bool filter_task(const __nv_bfloat16* __restrict__ w, uint8_t* U, int t, int lane, uint32_t ew, bool first, bool last, uint32_t* ready) {
  const int wg = t & 1, blk = (t >> 1) % 6, co = (t / 12) % 24, s = t / (12 * 24);
  const int k = blk * 32 + ((lane >> 1) & 3) * 8 + (lane >> 3) * 2 + (lane & 1);
  const unsigned short* wp = reinterpret_cast<const unsigned short*>(w) + ((wg * 6 + s) * CH + co * 8) * CH + k;
  const int dr = wg ? -3 * CH * CH : 3 * CH * CH;
  uint32_t g[3][8];
#pragma unroll
  for (int r = 0; r < 3; r++)
#pragma unroll
    for (int i = 0; i < 8; i++) asm volatile("ld.global.nc.u16 %0, [%1];" : "=r"(g[r][i]) : "l"(wp + r * dr + i * CH));
  const int chunk = co >> 2;
  uint8_t* const u = U + wg * UWG + (3 * ((co >> 1) & 1) + s) * UTILE + (blk * 4 + (lane >> 3)) * 256 + (co & 1) * 128 + (lane & 7) * 16;
  if (first) { cluster_wait(); asm volatile("bar.sync 11, 288;" ::: "memory"); }
  asm volatile("ld.shared.u32 %0, [%0];" : "+r"(ew)::"memory");
  const float su = __uint_as_float((249 - ew) << 23), low = __uint_as_float(15u << 23);
  const float na = (wg ? 128.f / 90.f : 1.f / 1.40625f) * low, sg = wg ? -1.f : 1.f;
  float v[5][8], m = 0.f;
#pragma unroll
  for (int i = 0; i < 8; i++) {
    const float a = __uint_as_float(g[0][i] << 16) * su, b = __uint_as_float(g[1][i] << 16) * su, c = __uint_as_float(g[2][i] << 16) * su;
    asm("{\n.reg .f32 t;\nmax.NaN.f32 t, %1, %2;\nmax.NaN.f32 %0, %0, %3;\nmax.NaN.f32 %0, %0, t;\n}" : "+f"(m) : "f"(fabsf(a)), "f"(fabsf(b)), "f"(fabsf(c)));
    const float e = fmaf(0.25f, c, a) * na, o = b * (0.5f * na), d = fmaf(a + c, sg, b);
    v[0][i] = e + o; v[1][i] = (e - o) * sg; v[2][i] = d * (low / -4.5f); v[3][i] = a * (-sg * low); v[4][i] = d * (0.5f * low);
  }
#pragma unroll
  for (int q = 0; q < 5; q++) {
    uint32_t pk[4];
#pragma unroll
    for (int i = 0; i < 4; i++) {
      asm("cvt.rn.bf16x2.f32 %0, %1, %2;" : "=r"(pk[i]) : "f"(v[q][2 * i + 1]), "f"(v[q][2 * i]));
      pk[i] += (pk[i] & 0x7FFF7FFFu) * 7;
    }
    *reinterpret_cast<uint4*>(u + 6 * group_of(q, chunk) * UTILE) = make_uint4(pk[0], pk[1], pk[2], pk[3]);
    if (q == 3) *reinterpret_cast<uint4*>(u + 6 * group_of(5, chunk) * UTILE) = make_uint4(pk[0], pk[1], pk[2], pk[3]);
    if (q == 1 && last) made(ready, 1);
  }
  return m < 0.1875f;
}

__device__ __forceinline__ uint32_t smem_u32(const void* p) { return (uint32_t)__cvta_generic_to_shared(p); }
__device__ __forceinline__ void mbar_init(uint32_t bar, uint32_t cnt) {
  asm volatile("mbarrier.init.shared::cta.b64 [%0], %1;" ::"r"(bar), "r"(cnt));
}
__device__ __forceinline__ void mbar_expect_tx(uint32_t bar, uint32_t bytes) {
  asm volatile("mbarrier.arrive.expect_tx.shared::cta.b64 _, [%0], %1;" ::"r"(bar), "r"(bytes) : "memory");
}
__device__ __forceinline__ void mbar_wait(uint32_t bar, uint32_t parity) {
  asm volatile(
      "{\n.reg .pred p;\n"
      "WAIT_%=:\n"
      "mbarrier.try_wait.parity.shared::cta.b64 p, [%0], %1;\n"
      "@p bra DONE_%=;\n"
      "bra WAIT_%=;\n"
      "DONE_%=:\n}" ::"r"(bar), "r"(parity) : "memory");
}
__device__ __forceinline__ uint32_t mbar_try(uint32_t bar, uint32_t parity) {
  uint32_t ok;
  asm volatile(
      "{\n.reg .pred p;\n"
      "mbarrier.test_wait.parity.shared::cta.b64 p, [%1], %2;\n"
      "selp.u32 %0, 1, 0, p;\n}" : "=r"(ok) : "r"(bar), "r"(parity) : "memory");
  return ok;
}
__device__ __forceinline__ void mbar_wait_sleep(uint32_t bar, uint32_t parity) {
  asm volatile(
      "{\n.reg .pred p;\n"
      "WAIT_%=:\n"
      "mbarrier.try_wait.parity.shared::cta.b64 p, [%0], %1, 20000;\n"
      "@p bra DONE_%=;\n"
      "bra WAIT_%=;\n"
      "DONE_%=:\n}" ::"r"(bar), "r"(parity) : "memory");
}
#undef mbar_wait
#undef mbar_wait_sleep
__device__ __forceinline__ void arrive_elect(uint32_t bar) {
  asm volatile(
      "{\n.reg .pred p;\n"
      "elect.sync _|p, 0xffffffff;\n"
      "@p mbarrier.arrive.shared::cta.b64 _, [%0];\n}" ::"r"(bar) : "memory");
}
__device__ __forceinline__ void cluster_sync() {
  asm volatile("barrier.cluster.arrive.relaxed.aligned;\nbarrier.cluster.wait.aligned;" ::: "memory");
}
__device__ __forceinline__ void wg_fence() { asm volatile("wgmma.fence.sync.aligned;" ::: "memory"); }
__device__ __forceinline__ void wg_commit() { asm volatile("wgmma.commit_group.sync.aligned;" ::: "memory"); }
template <int N> __device__ __forceinline__ void wg_wait() { asm volatile("wgmma.wait_group.sync.aligned %0;" ::"n"(N) : "memory"); }
template <int LEAD>
__device__ __forceinline__ void wgmma192(uint32_t (&d)[48], uint64_t adesc, uint64_t bdesc, uint32_t acc) {
  asm volatile(
      "{\n.reg .pred p;\n"
      "setp.ne.b32 p, %50, 0;\n"
      "wgmma.mma_async.sync.aligned.m64n192k16.f16.f16.f16 "
      "{%0,%1,%2,%3,%4,%5,%6,%7,%8,%9,%10,%11,%12,%13,%14,%15,%16,%17,%18,%19,%20,%21,%22,%23,%24,%25,%26,%27,%28,%29,%30,%31,%32,%33,%34,%35,%36,%37,%38,%39,%40,%41,%42,%43,%44,%45,%46,%47}, %48, %49, p, 1, 1, 0, 0;\n}\n"
      : "+r"(d[0]),"+r"(d[1]),"+r"(d[2]),"+r"(d[3]),"+r"(d[4]),"+r"(d[5]),"+r"(d[6]),"+r"(d[7]),"+r"(d[8]),"+r"(d[9]),"+r"(d[10]),"+r"(d[11]),"+r"(d[12]),"+r"(d[13]),"+r"(d[14]),"+r"(d[15]),"+r"(d[16]),"+r"(d[17]),"+r"(d[18]),"+r"(d[19]),"+r"(d[20]),"+r"(d[21]),"+r"(d[22]),"+r"(d[23]),"+r"(d[24]),"+r"(d[25]),"+r"(d[26]),"+r"(d[27]),"+r"(d[28]),"+r"(d[29]),"+r"(d[30]),"+r"(d[31]),"+r"(d[32]),"+r"(d[33]),"+r"(d[34]),"+r"(d[35]),"+r"(d[36]),"+r"(d[37]),"+r"(d[38]),"+r"(d[39]),"+r"(d[40]),"+r"(d[41]),"+r"(d[42]),"+r"(d[43]),"+r"(d[44]),"+r"(d[45]),"+r"(d[46]),"+r"(d[47])
      : "l"(adesc), "l"(bdesc), "r"(LEAD ? acc : 1u));
}

__device__ __forceinline__ void sts(uint32_t addr, uint32_t v) { asm volatile("st.shared.u32 [%0], %1;" ::"r"(addr), "r"(v) : "memory"); }
__device__ __forceinline__ void sts(uint32_t addr, uint2 v) { asm volatile("st.shared.v2.u32 [%0], {%1,%2};" ::"r"(addr), "r"(v.x), "r"(v.y) : "memory"); }
__device__ __forceinline__ void lds(uint32_t& v, uint32_t addr) { asm volatile("ld.shared.u32 %0, [%1];" : "=r"(v) : "r"(addr) : "memory"); }
__device__ __forceinline__ void lds(uint2& v, uint32_t addr) { asm volatile("ld.shared.v2.u32 {%0,%1}, [%2];" : "=r"(v.x), "=r"(v.y) : "r"(addr) : "memory"); }
__host__ __device__ constexpr uint32_t h2(uint32_t h) { return h | (h << 16); }
constexpr uint32_t H_2 = h2(0x4000), H_1_2 = h2(0x3800), H_1_4 = h2(0x3400), H_1_8 = h2(0x3000), H_1_16 = h2(0x2C00), H_1_32 = h2(0x2800),
                   H_N4 = h2(0xC400), H_N2 = h2(0xC000), H_N1_2 = h2(0xB800), H_N1_4 = h2(0xB400), H_N17_4 = h2(0xC440), H_1 = h2(0x3C00), H_N1 = h2(0xBC00);
__device__ __forceinline__ uint32_t hfma(uint32_t a, uint32_t b, uint32_t c) {
  uint32_t r; asm("fma.rn.f16x2 %0, %1, %2, %3;" : "=r"(r) : "r"(a), "r"(b), "r"(c)); return r;
}
__device__ __forceinline__ uint32_t hadd(uint32_t a, uint32_t b) { uint32_t r; asm("add.rn.f16x2 %0, %1, %2;" : "=r"(r) : "r"(a), "r"(b)); return r; }
__device__ __forceinline__ uint32_t hsub(uint32_t a, uint32_t b) { uint32_t r; asm("sub.rn.f16x2 %0, %1, %2;" : "=r"(r) : "r"(a), "r"(b)); return r; }
__device__ __forceinline__ uint2 hfma(uint2 a, uint32_t b, uint2 c) { return make_uint2(hfma(a.x, b, c.x), hfma(a.y, b, c.y)); }
__device__ __forceinline__ uint2 hadd(uint2 a, uint2 b) { return make_uint2(hadd(a.x, b.x), hadd(a.y, b.y)); }
__device__ __forceinline__ uint2 hsub(uint2 a, uint2 b) { return make_uint2(hsub(a.x, b.x), hsub(a.y, b.y)); }
__device__ __forceinline__ uint32_t bmul(uint32_t x, uint32_t k) { uint32_t z; asm("mul.rn.bf16x2 %0, %1, %2;" : "=r"(z) : "r"(x), "r"(k)); return z; }
__device__ __forceinline__ void scale(uint32_t& x, uint32_t k, uint32_t& m) { x = bmul(x, k); m |= x; }
__device__ __forceinline__ void scale(uint2& x, uint32_t k, uint32_t& m) {
  x.x = bmul(x.x, k); x.y = bmul(x.y, k);
  asm("lop3.b32 %0, %0, %1, %2, 0xFE;" : "+r"(m) : "r"(x.x), "r"(x.y));
}
__device__ __forceinline__ void tohalf(uint32_t& z) { z = (z & 0x7FFF7FFFu) * 7 + z; }
__device__ __forceinline__ void tohalf(uint2& z) { tohalf(z.x); tohalf(z.y); }
__device__ __forceinline__ bool out_of_range(uint32_t m) {
  m = __reduce_or_sync(0xffffffffu, m & 0x7FFF7FFFu);
  return (m & 0x78007800u) || (m && !(m & 0x06000600u));
}

template <typename V>
__device__ __forceinline__ void planes8(V (&d)[8], uint32_t dp, uint32_t dq, uint32_t dr, uint32_t ds) {
  const V ec = hfma(d[4], H_N17_4, hadd(d[6], d[2])), oc = hfma(d[3], H_N17_4, hadd(d[5], d[1]));
  sts(dr, hadd(ec, oc)); sts(dr + TWG, hsub(ec, oc));
#pragma unroll
  for (int k = 0; k < 6; k++) d[k] = hsub(d[k + 2], d[k]);
  const V ea = hfma(d[2], H_N4, d[4]), oa = hfma(d[1], H_N4, d[3]);
  sts(dp, hfma(oa, H_1_2, ea)); sts(dq, hfma(oa, H_N1_2, ea));
  sts(ds, hfma(hfma(d[0], H_N4, d[2]), H_N1_4, ea)); sts(ds + TWG, hfma(oa, H_N1_4, hfma(d[3], H_N4, d[5])));
  const V eb = hfma(d[2], H_N1_4, d[4]), ob = hfma(d[1], H_N1_4, d[3]);
  sts(dp + TWG, hfma(ob, H_2, eb)); sts(dq + TWG, hfma(ob, H_N2, eb));
}
template <typename V>
__device__ __forceinline__ void planes4(V (&d)[8], uint32_t dp, uint32_t dq) {
  sts(dp, hadd(d[2], d[1])); sts(dp + TWG, hsub(d[2], d[1]));
  sts(dq, hsub(d[2], d[0])); sts(dq + TWG, hsub(d[3], d[1]));
}

constexpr uint32_t BHI = 256 >> 4, BLO = (128 >> 4) << 16, AHI = 128 >> 4, ALO = (TCOL >> 4) << 16;
__device__ __forceinline__ uint64_t desc(uint32_t lo, uint32_t hi) { uint64_t d; asm("mov.b64 %0, {%1,%2};" : "=l"(d) : "r"(lo), "r"(hi)); return d; }

typedef uint32_t Acc[48];
struct Ctx {
  uint32_t sb;
  uint64_t ad, bd;
  uint32_t b0;
  uint32_t me, ra, tx;
  uint32_t ok;
  bool one;
  uint32_t wg, xs, xr;
  uint32_t w[12];
  uint32_t k, sg;
  const char* o;
  bool on, yes;
};
__device__ __forceinline__ void arrive(uint32_t bar, bool on) {
  asm volatile("{\n.reg .pred p;\nsetp.ne.b32 p, %1, 0;\n@p mbarrier.arrive.shared::cta.b64 _, [%0];\n}" ::"r"(bar), "r"((uint32_t)on) : "memory");
}
template <int S>
__device__ __forceinline__ void release(Ctx& C, uint32_t me, uint32_t tx) {
  asm volatile(
      "{\n.reg .pred p;\n"
      "setp.ne.b32 p, %1, 0;\n"
      "@p mbarrier.arrive.expect_tx.shared::cta.b64 _, [%0], %1;\n}" ::"r"(C.b0 + 16 * S), "r"(tx) : "memory");
  asm volatile(
      "{\n.reg .pred p;\n"
      "setp.eq.b32 p, %0, %2;\n"
      "@p mbarrier.arrive.shared::cluster.b64 _, [%1];\n}" ::"r"(me), "r"(C.ra), "n"(S) : "memory");
}
template <int SYNC, int ID0, int ID1>
__device__ __forceinline__ void bar(uint32_t wg) {
  if (SYNC) asm volatile("{\n.reg .pred p;\nsetp.ne.b32 p, %0, 0;\n@!p bar.sync %1, 256;\n@p bar.sync %2, 256;\n}" ::"r"(wg), "n"(ID0), "n"(ID1) : "memory");
  else asm volatile("{\n.reg .pred p;\nsetp.ne.b32 p, %0, 0;\n@!p bar.arrive %1, 256;\n@p bar.arrive %2, 256;\n}" ::"r"(wg), "n"(ID0), "n"(ID1) : "memory");
}
__device__ __forceinline__ void sent(Ctx& C) { bar<0, 1, 2>(C.wg); }
__device__ __forceinline__ void await_sent(Ctx& C) { bar<1, 2, 1>(C.wg); }
__device__ __forceinline__ void sent2(Ctx& C) { bar<0, 10, 11>(C.wg); }
__device__ __forceinline__ void await_sent2(Ctx& C) { bar<1, 11, 10>(C.wg); }
__device__ __forceinline__ void await_taken(Ctx& C) { bar<1, 3, 4>(C.wg); }
__device__ __forceinline__ void taken(Ctx& C, uint32_t x) { if ((x & blockIdx.y) == 0) bar<0, 4, 3>(C.wg); }

__host__ __device__ constexpr int xoff(int u, int h) { return u * TUNIT + h * 2048; }
template <int B, int OF>
__device__ __forceinline__ void send(const Acc& A, uint32_t addr) {
  asm volatile("st.shared.v4.u32 [%4 + %5], {%0,%1,%2,%3};" ::"r"(A[4 * B]), "r"(A[4 * B + 1]), "r"(A[4 * B + 2]), "r"(A[4 * B + 3]), "r"(addr), "n"(OF) : "memory");
}
template <int B, int OF>
__device__ __forceinline__ void recv(Acc& A, uint32_t addr, bool on) {
  asm volatile("{\n.reg .pred p;\nsetp.ne.b32 p, %6, 0;\n@p ld.shared.v4.u32 {%0,%1,%2,%3}, [%4 + %5];\n}"
               : "+r"(A[4 * B]), "+r"(A[4 * B + 1]), "+r"(A[4 * B + 2]), "+r"(A[4 * B + 3]) : "r"(addr), "n"(OF), "r"((uint32_t)on) : "memory");
}
template <int OF>
__device__ __forceinline__ void fetch4(uint32_t* w, uint32_t addr) {
  asm volatile("ld.shared.v4.u32 {%0,%1,%2,%3}, [%4 + %5];" : "=r"(w[0]), "=r"(w[1]), "=r"(w[2]), "=r"(w[3]) : "r"(addr), "n"(OF) : "memory");
}
template <int I, int N>
__device__ __forceinline__ void add_to(Acc& A, const uint32_t* w, uint32_t sg) {
#pragma unroll
  for (int j = 0; j < N; j++) asm volatile("fma.rn.f16x2 %0, %1, %2, %0;" : "+r"(A[I + j]) : "r"(w[j]), "r"(sg));
}
template <int I, int N>
__device__ __forceinline__ void join(Acc& A, const Acc& B) {
#pragma unroll
  for (int j = I; j < I + N; j++) asm volatile("add.rn.f16x2 %0, %0, %1;" : "+r"(A[j]) : "r"(B[j]));
}
template <int B, int OF>
__device__ __forceinline__ void split(Acc& A, const Acc& Bb, uint32_t* w, uint32_t addr) {
#pragma unroll
  for (int j = 0; j < 4; j++)
    asm volatile("sub.rn.f16x2 %0, %1, %2;\nadd.rn.f16x2 %1, %1, %2;" : "=&r"(w[j]), "+r"(A[4 * B + j]) : "r"(Bb[4 * B + j]));
  asm volatile("st.shared.v4.u32 [%4 + %5], {%0,%1,%2,%3};" ::"r"(w[0]), "r"(w[1]), "r"(w[2]), "r"(w[3]), "r"(addr), "n"(OF) : "memory");
}
__host__ __device__ constexpr int pj(int k) { return 2 * (k >> 2) + (k & 1); }
__host__ __device__ constexpr int pp(int k) { return (k >> 1) & 1; }
template <int K>
__device__ __forceinline__ void rows(const Acc& P, Acc& Q, Acc& R, uint32_t* w) {
#pragma unroll
  for (int i = 0; i < 4; i++) {
    const int j = 8 * pj(K) + 2 * i + pp(K);
    asm volatile(
        "{\n.reg .b32 a, b;\n"
        "fma.rn.f16x2 a, %1, %4, %2;\n fma.rn.f16x2 b, %1, %5, %2;\n fma.rn.f16x2 %1, %1, %6, %2;\n"
        "fma.rn.f16x2 %0, %3, %7, a;\n fma.rn.f16x2 %2, %3, %8, b;\n add.rn.f16x2 %1, %1, %3;\n}"
        : "=r"(w[i]), "+r"(Q[j]), "+r"(R[j]) : "r"(P[j]), "r"(H_1_8), "r"(H_1_2), "r"(H_1_32), "r"(H_1_4), "r"(H_1_16));
  }
}
__device__ __forceinline__ uint32_t tobf(uint32_t h, uint32_t k) {
  uint32_t o;
  asm volatile("{\n.reg .b16 l, u;\n.reg .f32 a, b;\n.reg .b32 t;\nmov.b32 {l, u}, %1;\ncvt.f32.f16 a, l;\ncvt.f32.f16 b, u;\n"
               "cvt.rn.bf16x2.f32 t, b, a;\nmul.rn.bf16x2 %0, t, %2;\n}" : "=r"(o) : "r"(h), "r"(k));
  return o;
}
template <int K>
__device__ __forceinline__ void stg4(const char* o, const uint32_t* r) {
  asm volatile("st.global.cs.v4.u32 [%4 + %5], {%0,%1,%2,%3};" ::"r"(r[0]), "r"(r[1]), "r"(r[2]), "r"(r[3]), "l"(o), "n"(pp(K) * 8 * CH * 2 + pj(K) * 64) : "memory");
}
template <int K, int LAST = 0>
__device__ __forceinline__ void put(const Acc& A, Ctx& C) {
  uint32_t* w = C.w + (LAST ? 4 * (K & 1) : 8);
#pragma unroll
  for (int i = 0; i < 4; i++) w[i] = tobf(A[8 * pj(K) + 2 * i + pp(K)], C.k);
  stg4<K>(C.o, w);
}

constexpr uint64_t OUT_R = 0x252949290ull, OUT_S = 0x084210842108421ull, OUT_M = 0x151551540ull, OUT_F = 0x281015555ull;
constexpr int E0_AT = 6, E1_AT = 27;
__host__ __device__ constexpr int below(uint64_t m, int n) { return __builtin_popcountll(m & ((1ull << n) - 1)); }
static_assert(below(OUT_R, 36) == 12 && below(OUT_S, 60) == 12 && below(OUT_M, 35) == 12 && below(OUT_F, 36) == 12, "pieces");
static_assert(!(OUT_R & 15) && !(OUT_M & 0xC03F) && !(OUT_M & (OUT_M << 1)) && below(OUT_M, 8) <= 1 && below(OUT_M, 12) <= 4 && below(OUT_M, 24) <= 8 && below(OUT_M, 28) <= 9 && !(OUT_F & 0x7E000000) && E0_AT >= 6 && E1_AT >= 27, "order");

__host__ __device__ constexpr int r_out(int n) { return n >= 96 && n < 100 ? n - 96 : n == 124 || n == 125 ? n - 120 : -1; }
__host__ __device__ constexpr int d_out(int n) { return n >= 108 && n < 112 ? n - 108 : n == 122 || n == 123 ? n - 118 : -1; }
__host__ __device__ constexpr int r_in(int n) { return n >= 101 && n < 109 ? n - 101 : n == 130 || n == 131 ? n - 122 : n == 134 || n == 135 ? n - 124 : -1; }
__host__ __device__ constexpr int d_in(int n) { return n >= 112 && n < 120 ? n - 112 : n == 128 || n == 129 ? n - 120 : n == 132 || n == 133 ? n - 122 : -1; }
constexpr uint32_t XU_R = 0x750354, XU_D = 0x425421, XU_F = 0x984210;
template <int N, int FILL>
__device__ __forceinline__ void early(Acc& P, Acc& Q, Acc& R, Acc& S, Ctx& C) {
  if constexpr (FILL) {
    constexpr int I = N - 61;
    if constexpr (I == 0) await_sent(C);
    if constexpr (I >= 0 && I < 6) { fetch4<xoff(unit(XU_F, I), 0)>(C.w, C.xr); fetch4<xoff(unit(XU_F, I), 1)>(C.w + 4, C.xr); }
  } else {
    if constexpr (N == 101 || N == 116) await_sent(C);
    if constexpr (N == 112 || N == 128) await_sent2(C);
    if constexpr (r_in(N) >= 0) {
      constexpr int B = r_in(N);
      fetch4<xoff(unit(XU_R, B / 2), B & 1)>(C.w + 4, C.xr);
    }
    if constexpr (d_in(N) >= 0) recv<d_in(N), xoff(unit(XU_D, d_in(N) / 2), d_in(N) & 1)>(Q, C.xr, C.yes);
  }
}
template <int N, int FILL>
__device__ __forceinline__ void side(Acc& P, Acc& Q, Acc& R, Acc& S, Ctx& C) {
  const uint32_t te = C.sb + BAR_TEMPTY;
  if constexpr (FILL) {
    constexpr int I = N - 36, X = N - 54;
    if constexpr ((OUT_F >> I) & 1) { if (C.on) put<below(OUT_F, I)>(S, C); }
    if constexpr (X >= 0 && X < 6) { send<2 * X, xoff(unit(XU_F, X), 0)>(P, C.xs); send<2 * X + 1, xoff(unit(XU_F, X), 1)>(P, C.xs); }
    if constexpr (X == 5) sent(C);
    if constexpr (N == 66) { if (C.wg) asm volatile("bar.sync 6, 256;" ::: "memory"); }
    if constexpr (N == 71) { if (!C.wg) asm volatile("bar.arrive 6, 256;" ::: "memory"); }
    if constexpr (N >= 61 && N < 67) { if (C.yes) add_to<8 * (N - 61), 8>(P, C.w, C.sg); }
  } else if constexpr (N < 36) {
    if constexpr (N == 0) arrive(te + 16, C.one);
    if constexpr (N < 4) { if (C.on) join<12 * N, 12>(S, Q); }
    if constexpr ((OUT_R >> N) & 1) { if (C.on) put<below(OUT_R, N)>(R, C); }
    if constexpr (N == 30) arrive(te + 24, C.one);
  } else if constexpr (N < 96) {
    if constexpr ((OUT_S >> (N - 36)) & 1) { if (C.on) put<below(OUT_S, N - 36)>(S, C); }
    if constexpr (N == 48) arrive(te + 32, C.one);
    if constexpr (N == 72) arrive(te + 40, C.one);
  } else {
    constexpr int I = N - 108;
    if constexpr (I > 0) {
      if constexpr ((OUT_M >> (I - 1)) & 1) {
        if (C.yes) {
#pragma unroll
          for (int i = 0; i < 4; i++) C.w[8 + i] = tobf(C.w[i], C.k);
        }
        stg4<below(OUT_M, I - 1)>(C.o, C.w + 8);
      }
    }
    if constexpr (I >= 0) {
      if constexpr ((OUT_M >> I) & 1) { if (C.yes) rows<below(OUT_M, I)>(P, Q, R, C.w); }
    }
    if constexpr (N == 110 || N == 122) await_taken(C);
    if constexpr (r_out(N) >= 0) {
      constexpr int X = r_out(N);
      send<2 * X, xoff(unit(XU_R, X), 0)>(R, C.xs); send<2 * X + 1, xoff(unit(XU_R, X), 1)>(R, C.xs);
    }
    if constexpr (r_in(N) >= 0) {
      if (C.yes) {
        add_to<4 * r_in(N), 4>(R, C.w + 4, C.sg);
      }
    }
    if constexpr (d_out(N) >= 0) {
      constexpr int X = d_out(N);
      if (C.yes) { split<2 * X, xoff(unit(XU_D, X), 0)>(P, Q, C.w + 4, C.xs); split<2 * X + 1, xoff(unit(XU_D, X), 1)>(P, Q, C.w, C.xs); }
    }
    if constexpr (N == 99 || N == 111) sent(C);
    if constexpr (N == 109 || N == 125) sent2(C);
    if constexpr (N == 108) taken(C, R[31]);
    if constexpr (N == 120) taken(C, Q[11] | Q[15] | Q[19] | Q[23] | Q[27] | Q[31]);
    if constexpr (I == E0_AT) arrive(te, C.one && ((Q[3] | Q[7]) & blockIdx.y) == 0);
    if constexpr (I == E1_AT) arrive(te + 8, C.one && ((R[47] | Q[35] | Q[39] | Q[43] | Q[47]) & blockIdx.y) == 0);
  }
}
template <int W, int LEAD, int N0, int FILL, int J = 0>
__device__ __forceinline__ void group(Acc& P, Acc& Q, Acc& R, Acc& S, Ctx& C, uint64_t a) {
  constexpr int N = N0 + J;
  if (!C.ok) mbar_wait(C.b0 + 16 * (N % NUST), (N / NUST) & 1);
  wg_fence();
  wgmma192<LEAD && J == 0>(W == 0 ? P : W == 1 ? Q : W == 2 ? R : S, a + (((J / 3) * 2 * TCOL + (J % 3) * 16) >> 4), C.bd + (N % NUST) * (UTILE >> 4), blockIdx.y);
  wg_commit();
  C.ok = mbar_try(C.b0 + 16 * ((N + 1) % NUST), ((N + 1) / NUST) & 1);
  early<N, FILL>(P, Q, R, S, C);
  wg_wait<1>();
  release<(N + NUST - 1) % NUST>(C, N || C.on ? C.me : 0, N || C.on ? C.tx : 0);
  side<N, FILL>(P, Q, R, S, C);
  if constexpr (J < 5) group<W, LEAD, N0, FILL, J + 1>(P, Q, R, S, C, a);
}

__device__ __forceinline__ void fetch(const CUtensorMap* map, uint32_t bytes, uint32_t dst, uint32_t bar, int c, int x, int y, uint64_t pol) {
  asm volatile("{\n.reg .pred p;\nelect.sync _|p, 0xffffffff;\n"
               "@p mbarrier.arrive.expect_tx.shared::cta.b64 _, [%2], %6;\n"
               "@p cp.async.bulk.tensor.3d.shared::cluster.global.mbarrier::complete_tx::bytes.L2::cache_hint [%0], [%1, {%3,%4,%5}], [%2], %7;\n}"
               ::"r"(dst), "l"(map), "r"(bar), "r"(c), "r"(x), "r"(y), "r"(bytes), "l"(pol) : "memory");
}
constexpr uint64_t POL_FIRST = 0x12F0000000000000ull, POL_SAME = 0x10F0000000000000ull;

struct Params { uint8_t* U; uint32_t* ready; int lg, ufirst, ustep, nunit, umax, nfill, s0, second, nfirst; uint4 un[12]; };

__global__ void __launch_bounds__(NTHREADS, 1) wino_main(const __grid_constant__ CUtensorMap xmap8, const __grid_constant__ CUtensorMap xmap4,
                                                         const __grid_constant__ CUtensorMap xmap1, const __grid_constant__ CUtensorMap xmap0,
                                                         const __nv_bfloat16* __restrict__ xin, const __nv_bfloat16* __restrict__ wgt,
                                                         __nv_bfloat16* __restrict__ out, const Params P) {
  extern __shared__ __align__(1024) uint8_t smem[];
  { const uint32_t l = threadIdx.x * gridDim.x + blockIdx.x; if (l < 9 * CH * CH * 2 / 128) asm volatile("prefetch.global.L2 [%0];" ::"l"((const char*)wgt + l * 128u)); }
  const uint32_t sb = smem_u32(smem);
  const int warp = __shfl_sync(0xffffffffu, threadIdx.x >> 5, 0), lane = threadIdx.x & 31;
  const uint32_t cm = (1u << P.lg) - 1, rank = blockIdx.x & cm;
  const int cl = blockIdx.x >> P.lg;
  if (P.nfill == 0) {
    asm volatile("griddepcontrol.wait;" ::: "memory");
    *P.ready = 0;
    return;
  }
  const int nit = min(P.umax, (P.nunit - cl * P.ufirst + P.ustep - 1) / P.ustep), fu = cl % P.nfill;
  auto first = [&](int i) {
    const int u = cl * P.ufirst + i * P.ustep, q = (u * (205 << (P.lg - 1))) >> 12;
    const int st = P.s0 + (i < nit ? q : fu >> (3 - P.lg));
    const int y = i < nit ? ((u - q * (40 >> P.lg)) * 6 << P.lg) + 6 * rank : 240 + ((fu & ((8 >> P.lg) - 1)) * 2 << P.lg) + 2 * rank;
    return (st & 7) * 64 + ((st >> 3) * 256 + y) * IMG;
  };

  auto origin = [&](int i) { int o; asm volatile("ld.shared.u32 %0, [%1];" : "=r"(o) : "r"(sb + SM_ORG + 4 * i)); return o; };
  if (warp == 11 && lane < 7) sts(sb + SM_ORG + 4 * lane, (uint32_t)first(min(lane, nit)));

  if (warp != 11) asm volatile("barrier.cluster.arrive.relaxed.aligned;" ::: "memory");
  if (warp == 10) {
    sts(sb + SM_EXP, min(sample_exp((const char*)wgt + lane * (4 * 5168), 5168), 240u));
    asm volatile("bar.arrive 11, 288;" ::: "memory");
  }
  if (warp == 9) {
    const uint32_t e = sample_exp((const char*)xin + ((uint32_t)(first(0) + 2 * lane + (lane & 1) * IMG) * (CH * 2u) + lane % 6 * 64), CH / 2 + 16);
    sts(sb + SM_EXP + 4, e ? min(e, 138u) : 120);
    asm volatile("bar.arrive 12, 192;\nbar.arrive 13, 288;" ::: "memory");
  }
  if (warp < 8) {
    const int t0 = warp * gridDim.x + blockIdx.x;
    if (P.second || t0 >= NFILT) { cluster_wait(); asm volatile("bar.sync 11, 288;" ::: "memory"); }
    if (!P.second) {
      bool ok = true;
      if (t0 >= NFILT) made(P.ready, 1);
#pragma unroll 1
      for (int t = t0; t < NFILT; t += 8 * gridDim.x) ok = filter_task(wgt, P.U, t, lane, sb + SM_EXP, t == t0, t + 8 * gridDim.x >= NFILT, P.ready) && ok;
      if (!ok) atomicOr(P.ready, 1u << 31);
      made(P.ready, 1024);
    }
  }
  if (warp == 8) {
    uint32_t v; asm volatile("ld.volatile.global.u32 %0, [%1];" : "=r"(v) : "l"(P.ready) : "memory");
    if (v < P.nfirst) __nanosleep(100);
  }
  if (threadIdx.x == 352) {
    for (int i = 0; i < 2 * NUST; i++) { mbar_init(sb + BAR_U + 16 * i, 1); mbar_init(sb + BAR_U + 16 * i + 8, cm + 1); }
    for (int i = 0; i < 6; i++) { mbar_init(sb + BAR_TFULL + 8 * i, 5); mbar_init(sb + BAR_TEMPTY + 8 * i, 8); }
    sts(sb + SM_FLAG, 0u);
    asm volatile("fence.mbarrier_init.release.cluster;" ::: "memory");
    for (int i = 0; i < 2 * NUST; i++) mbar_expect_tx(sb + BAR_U + 16 * i, UTILE);
  }
  const uint32_t rbar = __shfl_sync(0xffffffffu, sb + BAR_RFULL + (warp & 3) * 16, 0), rbuf = sb + SM_R + (warp & 3) * (2 * RSLOT);
  if (warp >= 12) {
    if (lane == 0) {
      mbar_init(rbar, 1); mbar_init(rbar + 8, 1);
      asm volatile("fence.mbarrier_init.release.cluster;" ::: "memory");
    }
    __syncwarp();
    if (!P.second) __nanosleep(300);
    const int o = first(0);
#pragma unroll
    for (int i = 0; i < 2; i++)
      fetch(nit ? &xmap0 : &xmap4, nit ? RSLOT : RSLOT / 2, rbuf + i * RSLOT, rbar + 8 * i, 0, (o & 511) - 1 + (warp & 3) * 16 + i * 4, (o >> 9) - 1, POL_SAME);
  }
  __syncwarp();
  if (warp == 11) asm volatile("barrier.cluster.arrive.relaxed.aligned;" ::: "memory");
  if (warp == 8 || warp > 10) cluster_wait();
  if (warp > 10) asm volatile("bar.sync 12, 192;" ::: "memory");
  if (warp < 8) asm volatile("bar.sync 13, 288;" ::: "memory");
  uint2 ex;
  lds(ex, sb + SM_EXP);
  const uint32_t kin = h2((139 - ex.y) << 7);

  if (warp >= 12) {
    asm volatile("setmaxnreg.dec.sync.aligned.u32 40;");
    const int wi = warp - 12;
    const uint32_t tb = __shfl_sync(0xffffffffu, sb + SM_T + ((lane >> 1) & 3) * TCOL + (wi * 16 + (lane >> 3)) * 16 + (lane & 1) * 8, lane);
    const uint32_t src = rbuf + __shfl_sync(0xffffffffu, lane * 8, lane);
    const uint32_t nb = __shfl_sync(0xffffffffu, lane & blockIdx.y, lane);
    int o = origin(0), x = (o & 511) - 1 + wi * 16, y = (o >> 9) - 1;
    uint32_t m = 0;
    auto chunk = [&](auto fill, int i, uint32_t c, int xn, int yn) {
      constexpr int NR = fill.value ? 4 : 8;
      const CUtensorMap* const map = fill.value ? &xmap4 : &xmap8;
      const uint4 un = P.un[6 * fill.value + c];
      const bool turn = c == 5, half = fill.value || (turn && i + 1 == nit);
      const CUtensorMap* const map1 = half ? &xmap4 : &xmap8;
      const int c1 = turn ? 0 : c * 32 + 32, x1 = turn ? xn : x, y1 = turn ? yn : y;
      const uint32_t n1 = half ? RSLOT / 2 : RSLOT;
#pragma unroll
      for (int q = 0; q < 4; q++) {
        const uint32_t sl = (q & 1) * RSLOT, rb = rbar + (q & 1) * 8;
        uint2 d[8];
        mbar_wait_sleep(rb, q >> 1);
#pragma unroll
        for (int r = 0; r < NR; r++) lds(d[r], src + sl + r * RROW);
#pragma unroll
        for (int r = 0; r < NR; r++) scale(d[r], kin, m);
        if (q < 2) fetch(!fill.value && i + c == 0 ? &xmap0 : map, NR * RROW | (m & nb), rbuf + sl, rb, c * 32, x + 8 + 4 * q, y, c & 1 ? POL_FIRST : POL_SAME);
        else if (!fill.value || !turn) fetch(map1, n1 | (m & nb), rbuf + sl, rb, c1, x1 + 4 * q - 8, y1, c & 1 ? POL_SAME : POL_FIRST);
#pragma unroll
        for (int r = 0; r < NR; r++) tohalf(d[r]);
        if (q == 0 && (!fill.value || c < 3)) mbar_wait_sleep(sb + BAR_TEMPTY + 8 * c, (i & 1) ^ (c < 2));
        if (q == 0 && wi == 0) TRACE(2, tn);
        const uint32_t t = tb + 64 * q;
        if (fill.value) planes4(d, t + un.x, t + un.y);
        else planes8(d, t + un.x, t + un.y, t + un.z, t + un.w);
      }
      if (turn) {
        if (out_of_range(m)) asm volatile("red.shared.or.b32 [%0], %1;" ::"r"(sb + SM_FLAG), "r"(1u << i) : "memory");
        m = 0; x = xn; y = yn;
      }
      asm volatile("fence.proxy.async.shared::cta;" ::: "memory");
      __syncwarp();
      arrive_elect(sb + BAR_TFULL + 8 * c);
    };
#pragma unroll 1
    for (int i = 0; i < nit; i++) {
      o = origin(i + 1);
#pragma unroll 1
      for (uint32_t c = 0; c < 6; c++) chunk(std::false_type(), i, c, (o & 511) - 1 + wi * 16, (o >> 9) - 1);
    }
#pragma unroll 1
    for (uint32_t c = 0; c < 6; c++) chunk(std::true_type(), nit, c, 0, 0);
    cluster_sync();
  } else if (warp >= 8) {
    asm volatile("setmaxnreg.dec.sync.aligned.u32 24;");
    if (warp < 10) {
      const uint32_t g = warp - 8, s0 = rank ^ (5 * g & cm);
      const uint32_t ring = sb + SM_U + g * (NUST * UTILE), ub = sb + BAR_U + g * (NUST * 16);
      auto ahead = [&](int i, uint32_t sl, int r) {
        const int o = origin(i), y = o >> 9, nr = i < nit ? 6 : 2;
        const int yy = r < nr ? y + r : -2;
        if ((r & 1) == g && r < nr)
          asm volatile("{\n.reg .pred p;\nelect.sync _|p, 0xffffffff;\n@p cp.async.bulk.prefetch.tensor.3d.L2.global [%0, {%1,%2,%3}];\n}" ::"l"(&xmap1), "r"(sl * 64), "r"((o & 511) - 1), "r"(yy) : "memory");
        if ((r & 1) != g && ((r == 0 && rank == 0) || (r + 1 == nr && rank == cm)))
          asm volatile("{\n.reg .pred p;\nelect.sync _|p, 0xffffffff;\n@p cp.async.bulk.prefetch.tensor.3d.L2.global [%0, {%1,%2,%3}];\n}" ::"l"(&xmap1), "r"(sl * 64), "r"((o & 511) - 1), "r"(r ? yy + 1 : yy - 1) : "memory");
      };
      if (warp == 8) {
        uint32_t v, i = 0;
        do { asm volatile("ld.acquire.gpu.global.u32 %0, [%1];" : "=r"(v) : "l"(P.ready) : "memory"); if (++i > 5000000u) __trap(); } while ((v & 1023) < P.nfirst);
        asm volatile("bar.arrive 7, 64;" ::: "memory");
      }
      asm volatile("bar.sync 9, 64;" ::: "memory");
      asm volatile("fence.proxy.async.global;" ::: "memory");
      uint32_t ph = 1;
#pragma unroll 1
      for (int i = 0; i <= nit; i++) {
        const uint8_t* from = P.U + g * UWG + (i < nit ? 0 : NROUND * NUST * UTILE);
#pragma unroll 1
        for (uint32_t t = 0; t < (i < nit ? NROUND : NFROUND); t++, ph ^= 1, from += NUST * UTILE) {
          if (i == 0 && t == 36 / NUST) asm volatile("bar.sync 8, 96;\nfence.proxy.async.global;" ::: "memory");
#pragma unroll 1
          for (uint32_t s = s0; s < NUST; s += cm + 1) {
            mbar_wait(ub + 16 * s + 8, ph);
            asm volatile(
                "{\n.reg .pred p;\n"
                "elect.sync _|p, 0xffffffff;\n"
                "@p cp.async.bulk.shared::cluster.global.mbarrier::complete_tx::bytes.multicast::cluster [%0], [%1], %2, [%4], %3;\n}"
                ::"r"(ring + s * UTILE), "l"(from + s * UTILE), "n"(UTILE), "h"((uint16_t)((2u << cm) - 1)), "r"(ub + 16 * s) : "memory");
            if (s == s0) {
              if (t - 1 < 6) ahead(i, 2, t - 1);
              if (i < nit && t - 6 < 6) ahead(i + 1, 0, t - 6);
              if (i < nit && t - 10 < 6) ahead(i + 1, 1, t - 10);
            }
            if (i < nit || t + 3 < NFROUND) {
              const uint8_t* a = from + ((int)s + (t + 3 < NROUND || i + 1 >= nit ? 3 : 3 - NROUND) * NUST) * UTILE;
              if (((cl + t) & 7) == 0 && !P.second)
                asm volatile("{\n.reg .pred p;\nelect.sync _|p, 0xffffffff;\n@p cp.async.bulk.prefetch.L2.global [%0], %1;\n}" ::"l"(a), "n"(UTILE) : "memory");
            }
          }
        }
      }
    } else if (warp == 10) {
      uint32_t v, i = 0;
      do { asm volatile("ld.acquire.gpu.global.u32 %0, [%1];" : "=r"(v) : "l"(P.ready) : "memory"); if (++i > 5000000u) __trap(); } while (((v >> 10) & 1023) < P.nfirst);
      if (v >> 31) asm volatile("red.shared.or.b32 [%0], %1;" ::"r"(sb + SM_FLAG), "r"(0xFFFFu) : "memory");
      __syncwarp();
      asm volatile("bar.arrive 8, 96;" ::: "memory");
      asm volatile("bar.sync 7, 64;" ::: "memory");
      if (P.second && lane == 0 && ((atomicAdd(P.ready, 1 << 20) >> 20) & 1023) == gridDim.x - 1) *P.ready = 0;
      asm volatile("griddepcontrol.launch_dependents;");
    } else {
      const uint32_t tb = sb + SM_T + ((lane >> 2) & 3) * TCOL + (64 + (lane >> 4)) * 16 + (lane & 3) * 4;
      uint32_t iph = 0;
#pragma unroll 1
      for (int i = 0; i <= nit; i++, iph ^= 1) {
        const int o = origin(i), x = (o & 511) + 63 + (lane >> 4), y = (o >> 9) - 1, nr = i < nit ? 8 : 4;
        const char* p = (const char*)xin + (uint32_t)(o + 63 + (lane >> 4)) * (CH * 2u) + (lane & 15) * 4;
        uint32_t m = 0;
#pragma unroll 1
        for (uint32_t c = 0; c < 6; c++, p += 64) {
          uint32_t d[8];
#pragma unroll
          for (int r = 0; r < 8; r++) {
            d[r] = 0;
            if (x < IMG && (uint32_t)(y + r) < IMG && r < nr) asm volatile("ld.global.nc.u32 %0, [%1];" : "=r"(d[r]) : "l"(p + (r - 1) * ROWB));
          }
#pragma unroll
          for (int r = 0; r < 8; r++) { scale(d[r], kin, m); tohalf(d[r]); }
          if (i < nit || c < 3) mbar_wait_sleep(sb + BAR_TEMPTY + 8 * c, iph ^ (c < 2));
          if (i < nit) planes8(d, tb + unit(UN_P, c) * TUNIT, tb + unit(UN_Q, c) * TUNIT, tb + unit(UN_R, c) * TUNIT, tb + unit(UN_S, c) * TUNIT);
          else planes4(d, tb + unit(UN_FP, c) * TUNIT, tb + unit(UN_FQ, c) * TUNIT);
          if (c == 5 && (m & 0x78007800u)) asm volatile("red.shared.or.b32 [%0], %1;" ::"r"(sb + SM_FLAG), "r"(1u << i) : "memory");
          asm volatile("fence.proxy.async.shared::cta;" ::: "memory");
          __syncwarp();
          arrive_elect(sb + BAR_TFULL + 8 * c);
        }
      }
      if (P.second == 2) asm volatile("griddepcontrol.wait;" ::: "memory");
    }
    __syncwarp();
    cluster_sync();
  } else {
    const uint32_t ek = ex.x ? ex.x + ex.y - 119 : 0;
    asm volatile("setmaxnreg.inc.sync.aligned.u32 224;");
    const int wg = warp >> 2;
    Ctx C;
    C.sb = sb; C.wg = wg;
    C.b0 = sb + BAR_U + wg * (NUST * 16);
    C.bd = desc(BLO + (((sb + SM_U + wg * (NUST * UTILE)) & 0x3FFFF) >> 4), BHI);
    C.ad = desc(ALO + (((sb + SM_T + wg * TWG) & 0x3FFFF) >> 4), AHI);
    C.me = __shfl_sync(0xffffffffu, threadIdx.x & 127, lane); C.tx = __shfl_sync(0xffffffffu, (threadIdx.x & 127) == 0 ? UTILE : 0, lane);
    asm volatile("mapa.shared::cluster.u32 %0, %1, %2;" : "=r"(C.ra) : "r"(C.b0 + 16 * lane + 8), "r"((lane ^ 5 * wg) & cm));
    C.ok = 0;
    const uint32_t t16 = __shfl_sync(0xffffffffu, (warp & 3) * 512 + lane * 16, lane);
    C.one = (t16 & 511) == 0;
    C.xs = sb + SM_T + wg * TWG + t16;
    C.xr = sb + SM_T + (wg ^ 1) * TWG + t16;
    C.k = h2(ek << 7); C.sg = wg ? H_1 : H_N1;
    C.yes = C.sb != gridDim.x;
    const int drow = wg ? -2 * ROWB : 2 * ROWB;
    const char* const ob = (const char*)out + (uint32_t)(((warp & 3) * 16 + (lane >> 2)) * CH + (lane & 3) * 8) * 2u;
    C.o = ob;
#pragma unroll
    for (int i = 0; i < 12; i++) C.w[i] = 0;

    Acc A0, A1, A2, A3;
#pragma unroll
    for (int j = 0; j < 48; j++) { A0[j] = 0; A1[j] = 0; A2[j] = 0; A3[j] = 0; }
#define G(W, LEAD, N0, FILL, U) group<W, LEAD, N0, FILL>(A0, A1, A2, A3, C, C.ad + (U) * (TUNIT >> 4))
    uint32_t ph = 0;
#pragma unroll 1
    for (int item = 0;; item++) {
      C.on = item != 0;
      if (P.second && item == 2) {
        const int wait = (5 - nit) * 28000 - 10000;
        uint32_t c0, c;
        asm volatile("mov.u32 %0, %%clock;" : "=r"(c0));
        do { __nanosleep(500); asm volatile("mov.u32 %0, %%clock;" : "=r"(c)); } while ((int)(c - c0) < wait);
      }
      C.ad += item & blockIdx.y; C.bd += item & blockIdx.y;
      mbar_wait(sb + BAR_TFULL, ph);
      G(0, 1, 0, 0, unit(UN_P, 0));
      G(1, 1, 6, 0, unit(UN_Q, 0));
      mbar_wait(sb + BAR_TFULL + 8, ph);
      G(0, 0, 12, 0, unit(UN_P, 1)); G(1, 0, 18, 0, unit(UN_Q, 1));
      mbar_wait(sb + BAR_TFULL + 16, ph);
      G(0, 0, 24, 0, unit(UN_P, 2)); G(1, 0, 30, 0, unit(UN_Q, 2));
      C.o -= 2 * drow;
      if (item == nit) break;
      G(2, 1, 36, 0, unit(UN_R, 0)); G(2, 0, 42, 0, unit(UN_R, 1)); G(2, 0, 48, 0, unit(UN_R, 2));
      mbar_wait(sb + BAR_TFULL + 24, ph);
      G(2, 0, 54, 0, unit(UN_R, 3)); G(0, 0, 60, 0, unit(UN_P, 3)); G(1, 0, 66, 0, unit(UN_Q, 3));
      mbar_wait(sb + BAR_TFULL + 32, ph);
      G(2, 0, 72, 0, unit(UN_R, 4)); G(0, 0, 78, 0, unit(UN_P, 4)); G(1, 0, 84, 0, unit(UN_Q, 4));
      mbar_wait(sb + BAR_TFULL + 40, ph);
      G(2, 0, 90, 0, unit(UN_R, 5)); G(0, 0, 96, 0, unit(UN_P, 5)); G(1, 0, 102, 0, unit(UN_Q, 5));
      ph ^= 1;
      C.o = ob + (uint32_t)(origin(item) + (2 + wg) * IMG) * (CH * 2u);
      G(3, 1, 108, 0, unit(UN_S, 0)); G(3, 0, 114, 0, unit(UN_S, 1)); G(3, 0, 120, 0, unit(UN_S, 2));
      G(3, 0, 126, 0, unit(UN_S, 3)); G(3, 0, 132, 0, unit(UN_S, 4)); G(3, 0, 138, 0, unit(UN_S, 5));
      C.o += drow;
    }
    mbar_wait(sb + BAR_TFULL + 24, ph);
    G(0, 0, 36, 1, unit(UN_FP, 3));
    mbar_wait(sb + BAR_TFULL + 32, ph);
    G(0, 0, 42, 1, unit(UN_FP, 4));
    mbar_wait(sb + BAR_TFULL + 40, ph);
    G(0, 0, 48, 1, unit(UN_FP, 5));
    G(1, 0, 54, 1, unit(UN_FQ, 3)); G(1, 0, 60, 1, unit(UN_FQ, 4)); G(1, 0, 66, 1, unit(UN_FQ, 5));
#undef G
    wg_wait<0>();
    uint32_t redo;
    asm volatile("ld.shared.u32 %0, [%1];" : "=r"(redo) : "r"(sb + SM_FLAG) : "memory");
    if (cl < P.nfill) {
      C.o = ob + (uint32_t)(origin(nit) + wg * IMG) * (CH * 2u);
      join<0, 48>(A1, A0);
      put<0, 1>(A1, C); put<1, 1>(A1, C); put<2, 1>(A1, C); put<3, 1>(A1, C); put<4, 1>(A1, C); put<5, 1>(A1, C);
      put<6, 1>(A1, C); put<7, 1>(A1, C); put<8, 1>(A1, C); put<9, 1>(A1, C); put<10, 1>(A1, C); put<11, 1>(A1, C);
    }
    if (ek - 1 > 253) redo = 0xFFFF;
    if (redo) {
      asm volatile("bar.sync 5, 256;" ::: "memory");
      const int k = threadIdx.x;
#pragma unroll 1
      for (int i = 0; i < nit + (cl < P.nfill); i++) {
        if (!((redo >> i) & 1) || k >= CH) continue;
        const int o = origin(i);
#pragma unroll 1
        for (int t = 0; t < (i < nit ? 48 : 16); t++) {
          const int y = (o >> 9) + (t >> 3), x = (o & 511) + (t & 7) * 8;
          float acc[8];
#pragma unroll
          for (int j = 0; j < 8; j++) acc[j] = 0.f;
#pragma unroll 1
          for (int rs = 0; rs < 9; rs++) {
            const int yy = y + rs / 3 - 1, xx = x + rs % 3 - 1;
            if ((uint32_t)yy >= IMG) continue;
#pragma unroll 1
            for (int c = 0; c < CH; c += 2) {
              const float w0 = __bfloat162float(wgt[(rs * CH + c) * CH + k]), w1 = __bfloat162float(wgt[(rs * CH + c + 1) * CH + k]);
#pragma unroll
              for (int j = 0; j < 8; j++) {
                if ((uint32_t)(xx + j) < IMG) {
                  const uint32_t v = __ldg(reinterpret_cast<const uint32_t*>(xin + (yy * IMG + xx + j) * CH + c));
                  acc[j] = fmaf(__uint_as_float(v & 0xFFFF0000u), w1, fmaf(__uint_as_float(v << 16), w0, acc[j]));
                }
              }
            }
          }
#pragma unroll
          for (int j = 0; j < 8; j++) out[(y * IMG + x + j) * CH + k] = __float2bfloat16(acc[j]);
        }
      }
    }
    __syncwarp();
    cluster_sync();
  }
}

typedef CUresult (*EncFn)(CUtensorMap*, CUtensorMapDataType, cuuint32_t, void*, const cuuint64_t*, const cuuint64_t*,
                          const cuuint32_t*, const cuuint32_t*, CUtensorMapInterleave, CUtensorMapSwizzle,
                          CUtensorMapL2promotion, CUtensorMapFloatOOBfill);

}

extern "C" void kernel_launch(void* const* d_in, const int* in_sizes, int n_in, void* d_out, int out_size) {
  const __nv_bfloat16* x = (const __nv_bfloat16*)d_in[0];
  const __nv_bfloat16* w = (const __nv_bfloat16*)d_in[1];
  __nv_bfloat16* out = (__nv_bfloat16*)d_out;

  static EncFn enc = nullptr;
  static void *U = nullptr, *ready = nullptr;
  if (!enc) {
    cudaGetSymbolAddress(&U, g_U);
    cudaGetSymbolAddress(&ready, g_ready);
    void* fn = nullptr; cudaDriverEntryPointQueryResult st;
    cudaGetDriverEntryPoint("cuTensorMapEncodeTiled", &fn, cudaEnableDefault, &st);
    enc = (EncFn)fn;
    cudaFuncSetAttribute(wino_main, cudaFuncAttributeMaxDynamicSharedMemorySize, SMEM_BYTES);
  }
  CUtensorMap xmap[4];
  for (int i = 0; i < 4; i++) {
    cuuint64_t dims[3] = {CH, IMG, IMG};
    cuuint64_t str[2] = {CH * 2, (cuuint64_t)ROWB};
    cuuint32_t box[3] = {i != 2 ? 32u : 64u, i != 2 ? 4u : 66u, i == 2 ? 1u : i == 1 ? 4u : 8u};
    cuuint32_t es[3] = {1, 1, 1};
    enc(&xmap[i], CU_TENSOR_MAP_DATA_TYPE_BFLOAT16, 3, (void*)x, dims, str, box, es, CU_TENSOR_MAP_INTERLEAVE_NONE,
        CU_TENSOR_MAP_SWIZZLE_NONE, i == 3 ? CU_TENSOR_MAP_L2_PROMOTION_NONE : CU_TENSOR_MAP_L2_PROMOTION_L2_128B, CU_TENSOR_MAP_FLOAT_OOB_FILL_NONE);
  }
  cudaLaunchConfig_t cfg = {};
  cudaLaunchAttribute attr[2];
  cfg.blockDim = dim3(NTHREADS);
  cfg.dynamicSmemBytes = SMEM_BYTES;
  cfg.stream = cudaStreamPerThread;
  attr[0].id = cudaLaunchAttributeClusterDimension;
  attr[0].val.clusterDim.x = 1 << LGA; attr[0].val.clusterDim.y = 1; attr[0].val.clusterDim.z = 1;
  attr[1].id = cudaLaunchAttributeProgrammaticStreamSerialization;
  attr[1].val.programmaticStreamSerializationAllowed = 1;
  cfg.attrs = attr;
  static int nca = 0, ncb = 0;
  if (!nca) {
    int n = 0, n2 = 0;
    cfg.numAttrs = 1;
    cfg.gridDim = dim3(128);
    cudaOccupancyMaxActiveClusters(&n, wino_main, &cfg);
    attr[0].val.clusterDim.x = 2;
    cudaOccupancyMaxActiveClusters(&n2, wino_main, &cfg);
    attr[0].val.clusterDim.x = 1 << LGA;
    nca = n < 1 ? 1 : n > 16 ? 16 : n;
    ncb = n2 - (nca << LGA) / 2;
  }
  cfg.numAttrs = 1;
  cfg.gridDim = dim3(nca << LGA);
  Params P = {(uint8_t*)U, (uint32_t*)ready, LGA, 5, 1, 5 * nca, 5, nca, 0, 0, nca << LGA};
  for (int c = 0; c < 6; c++) {
    P.un[c] = make_uint4(unit(UN_P, c) * TUNIT, unit(UN_Q, c) * TUNIT, unit(UN_R, c) * TUNIT, unit(UN_S, c) * TUNIT);
    P.un[6 + c] = make_uint4(unit(UN_FP, c) * TUNIT, unit(UN_FQ, c) * TUNIT, 0, 0);
  }
  cudaLaunchKernelEx(&cfg, wino_main, xmap[0], xmap[1], xmap[2], xmap[3], x, w, out, P);
  const int nf = 4 * (16 - nca), nb = nf == 0 ? 1 : ncb < nf ? nf : ncb > 5 * nf ? 5 * nf : ncb;
  attr[0].val.clusterDim.x = 2;
  cfg.numAttrs = 2;
  cfg.gridDim = dim3(2 * nb);
  cudaStreamCaptureStatus cap = cudaStreamCaptureStatusNone;
  cudaStreamIsCapturing(cfg.stream, &cap);
  P.lg = 1; P.ufirst = 1; P.ustep = nb; P.nunit = 5 * nf; P.nfill = nf; P.s0 = nca; P.second = cap == cudaStreamCaptureStatusActive ? 1 : 2;
  cudaLaunchKernelEx(&cfg, wino_main, xmap[0], xmap[1], xmap[2], xmap[3], x, w, out, P);
}
```

```cpp
#include <cuda_runtime.h>
#include <cuda.h>
#include <cuda_bf16.h>
#include <stdint.h>
#include <type_traits>

namespace {

constexpr int IMG = 512;
constexpr int CH = 192;
constexpr int ROWB = IMG * CH * 2;
constexpr int TCOL = 66 * 16;
constexpr int TUNIT = 4 * TCOL;
constexpr int TWG = 12 * TUNIT;
constexpr int RROW = 4 * 64;
constexpr int RSLOT = 8 * RROW;
constexpr int UTILE = 192 * 32;
constexpr int NUST = 9;
constexpr int NROUND = 144 / NUST, NFROUND = 72 / NUST;
constexpr int UWG = (NROUND + NFROUND) * NUST * UTILE;
constexpr int SM_U = 0;
constexpr int SM_R = SM_U + 2 * NUST * UTILE;
constexpr int SM_T = 131072 - 1024;
constexpr int SM_BAR = SM_T + 2 * TWG;
static_assert(SM_R + 4 * 2 * RSLOT <= SM_T, "smem");
constexpr int SMEM_BYTES = SM_BAR + 256 + 32 * NUST + 16;
constexpr int NTHREADS = 512;
constexpr int LGA = 3;
constexpr uint32_t BAR_TFULL = SM_BAR, BAR_TEMPTY = SM_BAR + 48, SM_FLAG = SM_BAR + 96, SM_ORG = SM_BAR + 100, SM_EXP = SM_BAR + 256 + 32 * NUST, BAR_RFULL = SM_BAR + 128,
                   BAR_U = SM_BAR + 256;
static_assert(SMEM_BYTES <= 232448 && SM_R % 128 == 0, "smem");

__host__ __device__ constexpr int group_of(int q, int c) {
  return q == 0 ? (c < 3 ? 2 * c : 3 * c + 1) : q == 1 ? (c < 3 ? 2 * c + 1 : 3 * c + 2) : q == 2 ? (c < 3 ? 6 + c : 3 * c) : q == 3 ? 18 + c
       : q == 4 ? 24 + (c < 3 ? 2 * c : 3 + c) : 24 + (c < 3 ? 2 * c + 1 : 6 + c);
}
constexpr uint32_t UN_P = 0x141820, UN_Q = 0x252941, UN_R = 0x030A53, UN_S = 0xA98B76, UN_FP = 0xA53820, UN_FQ = 0xB76941;
__host__ __device__ constexpr uint32_t unit(uint32_t tab, int c) { return (tab >> (4 * c)) & 15; }

__device__ __align__(1024) uint8_t g_U[2 * UWG];
__device__ uint32_t g_ready;
#define TRACE(row, i)

__device__ __forceinline__ void cluster_wait() { asm volatile("barrier.cluster.wait.acquire.aligned;" ::: "memory"); }
__device__ __forceinline__ uint32_t sample_exp(const char* p, uint32_t stride) {
  uint32_t m = 0;
  uint4 v[4];
#pragma unroll
  for (int i = 0; i < 4; i++)
    asm volatile("ld.global.nc.v4.u32 {%0,%1,%2,%3}, [%4];" : "=r"(v[i].x), "=r"(v[i].y), "=r"(v[i].z), "=r"(v[i].w) : "l"(p + i * stride));
  cluster_wait();
#pragma unroll
  for (int i = 0; i < 4; i++)
    m = __vmaxu2(__vmaxu2(m, __vmaxu2(v[i].x & 0x7FFF7FFFu, v[i].y & 0x7FFF7FFFu)), __vmaxu2(v[i].z & 0x7FFF7FFFu, v[i].w & 0x7FFF7FFFu));
  return __reduce_max_sync(0xffffffffu, max(m & 0xFFFFu, m >> 16)) >> 7;
}

#define PQBITS 9
constexpr int NFILT = 2 * 6 * 24 * 3;
__device__ __forceinline__ void made(uint32_t* ready, uint32_t n) {
  asm volatile("fence.proxy.async.global;\nbar.sync 10, 256;" ::: "memory");
  if (threadIdx.x == 0) asm volatile("red.release.gpu.global.add.u32 [%0], %1;" ::"l"(ready), "r"(n) : "memory");
  __syncwarp();
}
__device__ __forceinline__ bool filter_task(const __nv_bfloat16* __restrict__ w, uint8_t* U, int t, int lane, uint32_t ew, bool first, bool last, uint32_t* ready) {
  const int wg = t & 1, blk = (t >> 1) % 6, co = (t / 12) % 24, s = t / (12 * 24);
  const int k = blk * 32 + ((lane >> 1) & 3) * 8 + (lane >> 3) * 2 + (lane & 1);
  const unsigned short* wp = reinterpret_cast<const unsigned short*>(w) + ((wg * 6 + s) * CH + co * 8) * CH + k;
  const int dr = wg ? -3 * CH * CH : 3 * CH * CH;
  uint32_t g[3][8];
#pragma unroll
  for (int r = 0; r < 3; r++)
#pragma unroll
    for (int i = 0; i < 8; i++) asm volatile("ld.global.nc.u16 %0, [%1];" : "=r"(g[r][i]) : "l"(wp + r * dr + i * CH));
  const int chunk = co >> 2;
  uint8_t* const u = U + wg * UWG + (3 * ((co >> 1) & 1) + s) * UTILE + (blk * 4 + (lane >> 3)) * 256 + (co & 1) * 128 + (lane & 7) * 16;
  if (first) { cluster_wait(); asm volatile("bar.sync 11, 288;" ::: "memory"); }
  asm volatile("ld.shared.u32 %0, [%0];" : "+r"(ew)::"memory");
  const float su = __uint_as_float((249 - ew) << 23), low = __uint_as_float(15u << 23);
  const float na = wg ? 128.f / 90.f : 1.f / 1.40625f, sg = wg ? -1.f : 1.f;
  float v[5][8], m = 0.f;
#pragma unroll
  for (int i = 0; i < 8; i++) {
    const float a = __uint_as_float(g[0][i] << 16) * su, b = __uint_as_float(g[1][i] << 16) * su, c = __uint_as_float(g[2][i] << 16) * su;
    asm("{\n.reg .f32 t;\nmax.NaN.f32 t, %1, %2;\nmax.NaN.f32 %0, %0, %3;\nmax.NaN.f32 %0, %0, t;\n}" : "+f"(m) : "f"(fabsf(a)), "f"(fabsf(b)), "f"(fabsf(c)));
    const float e = fmaf(0.25f, c, a) * na, o = b * (0.5f * na), d = fmaf(a + c, sg, b);
    v[0][i] = e + o; v[1][i] = (e - o) * sg; v[2][i] = d * (low / -4.5f); v[3][i] = a * (-sg * low); v[4][i] = d * (0.5f * low);
  }
#pragma unroll
  for (int q = 0; q < 5; q++) {
    uint32_t pk[4];
#pragma unroll
    for (int i = 0; i < 4; i++) {
      if (q < 2) {
        asm("cvt.rz.f16x2.f32 %0, %1, %2;" : "=r"(pk[i]) : "f"(v[q][2 * i + 1]), "f"(v[q][2 * i]));
        pk[i] = (pk[i] + (0x00010001u << (10 - PQBITS))) & ~((0x00010001u << (11 - PQBITS)) - 0x00010001u);
      } else {
        asm("cvt.rn.bf16x2.f32 %0, %1, %2;" : "=r"(pk[i]) : "f"(v[q][2 * i + 1]), "f"(v[q][2 * i]));
        pk[i] += (pk[i] & 0x7FFF7FFFu) * 7;
      }
    }
    *reinterpret_cast<uint4*>(u + 6 * group_of(q, chunk) * UTILE) = make_uint4(pk[0], pk[1], pk[2], pk[3]);
    if (q == 3) *reinterpret_cast<uint4*>(u + 6 * group_of(5, chunk) * UTILE) = make_uint4(pk[0], pk[1], pk[2], pk[3]);
    if (q == 1 && last) made(ready, 1);
  }
  return m < 0.1875f;
}

__device__ __forceinline__ uint32_t smem_u32(const void* p) { return (uint32_t)__cvta_generic_to_shared(p); }
__device__ __forceinline__ void mbar_init(uint32_t bar, uint32_t cnt) {
  asm volatile("mbarrier.init.shared::cta.b64 [%0], %1;" ::"r"(bar), "r"(cnt));
}
__device__ __forceinline__ void mbar_expect_tx(uint32_t bar, uint32_t bytes) {
  asm volatile("mbarrier.arrive.expect_tx.shared::cta.b64 _, [%0], %1;" ::"r"(bar), "r"(bytes) : "memory");
}
__device__ __forceinline__ void mbar_wait(uint32_t bar, uint32_t parity) {
  asm volatile(
      "{\n.reg .pred p;\n"
      "WAIT_%=:\n"
      "mbarrier.try_wait.parity.shared::cta.b64 p, [%0], %1;\n"
      "@p bra DONE_%=;\n"
      "bra WAIT_%=;\n"
      "DONE_%=:\n}" ::"r"(bar), "r"(parity) : "memory");
}
__device__ __forceinline__ uint32_t mbar_try(uint32_t bar, uint32_t parity) {
  uint32_t ok;
  asm volatile(
      "{\n.reg .pred p;\n"
      "mbarrier.test_wait.parity.shared::cta.b64 p, [%1], %2;\n"
      "selp.u32 %0, 1, 0, p;\n}" : "=r"(ok) : "r"(bar), "r"(parity) : "memory");
  return ok;
}
__device__ __forceinline__ void mbar_wait_sleep(uint32_t bar, uint32_t parity) {
  asm volatile(
      "{\n.reg .pred p;\n"
      "WAIT_%=:\n"
      "mbarrier.try_wait.parity.shared::cta.b64 p, [%0], %1, 20000;\n"
      "@p bra DONE_%=;\n"
      "bra WAIT_%=;\n"
      "DONE_%=:\n}" ::"r"(bar), "r"(parity) : "memory");
}
#undef mbar_wait
#undef mbar_wait_sleep
__device__ __forceinline__ void arrive_elect(uint32_t bar) {
  asm volatile(
      "{\n.reg .pred p;\n"
      "elect.sync _|p, 0xffffffff;\n"
      "@p mbarrier.arrive.shared::cta.b64 _, [%0];\n}" ::"r"(bar) : "memory");
}
__device__ __forceinline__ void cluster_sync() {
  asm volatile("barrier.cluster.arrive.relaxed.aligned;\nbarrier.cluster.wait.aligned;" ::: "memory");
}
__device__ __forceinline__ void wg_fence() { asm volatile("wgmma.fence.sync.aligned;" ::: "memory"); }
__device__ __forceinline__ void wg_commit() { asm volatile("wgmma.commit_group.sync.aligned;" ::: "memory"); }
template <int N> __device__ __forceinline__ void wg_wait() { asm volatile("wgmma.wait_group.sync.aligned %0;" ::"n"(N) : "memory"); }
template <int LEAD>
__device__ __forceinline__ void wgmma192(uint32_t (&d)[48], uint64_t adesc, uint64_t bdesc, uint32_t acc) {
  asm volatile(
      "{\n.reg .pred p;\n"
      "setp.ne.b32 p, %50, 0;\n"
      "wgmma.mma_async.sync.aligned.m64n192k16.f16.f16.f16 "
      "{%0,%1,%2,%3,%4,%5,%6,%7,%8,%9,%10,%11,%12,%13,%14,%15,%16,%17,%18,%19,%20,%21,%22,%23,%24,%25,%26,%27,%28,%29,%30,%31,%32,%33,%34,%35,%36,%37,%38,%39,%40,%41,%42,%43,%44,%45,%46,%47}, %48, %49, p, 1, 1, 0, 0;\n}\n"
      : "+r"(d[0]),"+r"(d[1]),"+r"(d[2]),"+r"(d[3]),"+r"(d[4]),"+r"(d[5]),"+r"(d[6]),"+r"(d[7]),"+r"(d[8]),"+r"(d[9]),"+r"(d[10]),"+r"(d[11]),"+r"(d[12]),"+r"(d[13]),"+r"(d[14]),"+r"(d[15]),"+r"(d[16]),"+r"(d[17]),"+r"(d[18]),"+r"(d[19]),"+r"(d[20]),"+r"(d[21]),"+r"(d[22]),"+r"(d[23]),"+r"(d[24]),"+r"(d[25]),"+r"(d[26]),"+r"(d[27]),"+r"(d[28]),"+r"(d[29]),"+r"(d[30]),"+r"(d[31]),"+r"(d[32]),"+r"(d[33]),"+r"(d[34]),"+r"(d[35]),"+r"(d[36]),"+r"(d[37]),"+r"(d[38]),"+r"(d[39]),"+r"(d[40]),"+r"(d[41]),"+r"(d[42]),"+r"(d[43]),"+r"(d[44]),"+r"(d[45]),"+r"(d[46]),"+r"(d[47])
      : "l"(adesc), "l"(bdesc), "r"(LEAD ? acc : 1u));
}

__device__ __forceinline__ void sts(uint32_t addr, uint32_t v) { asm volatile("st.shared.u32 [%0], %1;" ::"r"(addr), "r"(v) : "memory"); }
__device__ __forceinline__ void sts(uint32_t addr, uint2 v) { asm volatile("st.shared.v2.u32 [%0], {%1,%2};" ::"r"(addr), "r"(v.x), "r"(v.y) : "memory"); }
__device__ __forceinline__ void lds(uint32_t& v, uint32_t addr) { asm volatile("ld.shared.u32 %0, [%1];" : "=r"(v) : "r"(addr) : "memory"); }
__device__ __forceinline__ void lds(uint2& v, uint32_t addr) { asm volatile("ld.shared.v2.u32 {%0,%1}, [%2];" : "=r"(v.x), "=r"(v.y) : "r"(addr) : "memory"); }
__host__ __device__ constexpr uint32_t h2(uint32_t h) { return h | (h << 16); }
constexpr uint32_t H_2 = h2(0x4000), H_1_2 = h2(0x3800), H_1_4 = h2(0x3400), H_1_8 = h2(0x3000), H_1_16 = h2(0x2C00), H_1_32 = h2(0x2800),
                   H_N4 = h2(0xC400), H_N2 = h2(0xC000), H_N1_2 = h2(0xB800), H_N1_4 = h2(0xB400), H_N17_4 = h2(0xC440), H_1 = h2(0x3C00), H_N1 = h2(0xBC00);
__device__ __forceinline__ uint32_t hfma(uint32_t a, uint32_t b, uint32_t c) {
  uint32_t r; asm("fma.rn.f16x2 %0, %1, %2, %3;" : "=r"(r) : "r"(a), "r"(b), "r"(c)); return r;
}
__device__ __forceinline__ uint32_t hadd(uint32_t a, uint32_t b) { uint32_t r; asm("add.rn.f16x2 %0, %1, %2;" : "=r"(r) : "r"(a), "r"(b)); return r; }
__device__ __forceinline__ uint32_t hsub(uint32_t a, uint32_t b) { uint32_t r; asm("sub.rn.f16x2 %0, %1, %2;" : "=r"(r) : "r"(a), "r"(b)); return r; }
__device__ __forceinline__ uint2 hfma(uint2 a, uint32_t b, uint2 c) { return make_uint2(hfma(a.x, b, c.x), hfma(a.y, b, c.y)); }
__device__ __forceinline__ uint2 hadd(uint2 a, uint2 b) { return make_uint2(hadd(a.x, b.x), hadd(a.y, b.y)); }
__device__ __forceinline__ uint2 hsub(uint2 a, uint2 b) { return make_uint2(hsub(a.x, b.x), hsub(a.y, b.y)); }
__device__ __forceinline__ uint32_t bmul(uint32_t x, uint32_t k) { uint32_t z; asm("mul.rn.bf16x2 %0, %1, %2;" : "=r"(z) : "r"(x), "r"(k)); return z; }
__device__ __forceinline__ void scale(uint32_t& x, uint32_t k, uint32_t& m) { x = bmul(x, k); m |= x; }
__device__ __forceinline__ void scale(uint2& x, uint32_t k, uint32_t& m) {
  x.x = bmul(x.x, k); x.y = bmul(x.y, k);
  asm("lop3.b32 %0, %0, %1, %2, 0xFE;" : "+r"(m) : "r"(x.x), "r"(x.y));
}
__device__ __forceinline__ void tohalf(uint32_t& z) { z = (z & 0x7FFF7FFFu) * 7 + z; }
__device__ __forceinline__ void tohalf(uint2& z) { tohalf(z.x); tohalf(z.y); }
__device__ __forceinline__ bool out_of_range(uint32_t m) {
  m = __reduce_or_sync(0xffffffffu, m & 0x7FFF7FFFu);
  return (m & 0x78007800u) || (m && !(m & 0x06000600u));
}

template <typename V>
__device__ __forceinline__ void planes8(V (&d)[8], uint32_t dp, uint32_t dq, uint32_t dr, uint32_t ds) {
  const V ec = hfma(d[4], H_N17_4, hadd(d[6], d[2])), oc = hfma(d[3], H_N17_4, hadd(d[5], d[1]));
  sts(dr, hadd(ec, oc)); sts(dr + TWG, hsub(ec, oc));
#pragma unroll
  for (int k = 0; k < 6; k++) d[k] = hsub(d[k + 2], d[k]);
  const V ea = hfma(d[2], H_N4, d[4]), oa = hfma(d[1], H_N4, d[3]);
  sts(dp, hfma(oa, H_1_2, ea)); sts(dq, hfma(oa, H_N1_2, ea));
  sts(ds, hfma(hfma(d[0], H_N4, d[2]), H_N1_4, ea)); sts(ds + TWG, hfma(oa, H_N1_4, hfma(d[3], H_N4, d[5])));
  const V eb = hfma(d[2], H_N1_4, d[4]), ob = hfma(d[1], H_N1_4, d[3]);
  sts(dp + TWG, hfma(ob, H_2, eb)); sts(dq + TWG, hfma(ob, H_N2, eb));
}
template <typename V>
__device__ __forceinline__ void planes4(V (&d)[8], uint32_t dp, uint32_t dq) {
  sts(dp, hadd(d[2], d[1])); sts(dp + TWG, hsub(d[2], d[1]));
  sts(dq, hsub(d[2], d[0])); sts(dq + TWG, hsub(d[3], d[1]));
}

constexpr uint32_t BHI = 256 >> 4, BLO = (128 >> 4) << 16, AHI = 128 >> 4, ALO = (TCOL >> 4) << 16;
__device__ __forceinline__ uint64_t desc(uint32_t lo, uint32_t hi) { uint64_t d; asm("mov.b64 %0, {%1,%2};" : "=l"(d) : "r"(lo), "r"(hi)); return d; }

typedef uint32_t Acc[48];
struct Ctx {
  uint32_t sb;
  uint64_t ad, bd;
  uint32_t b0;
  uint32_t me, ra, tx;
  uint32_t ok;
  bool one;
  uint32_t wg, xs, xr;
  uint32_t w[12];
  uint32_t k, sg;
  const char* o;
  bool on, yes;
};
__device__ __forceinline__ void arrive(uint32_t bar, bool on) {
  asm volatile("{\n.reg .pred p;\nsetp.ne.b32 p, %1, 0;\n@p mbarrier.arrive.shared::cta.b64 _, [%0];\n}" ::"r"(bar), "r"((uint32_t)on) : "memory");
}
template <int S>
__device__ __forceinline__ void release(Ctx& C, uint32_t me, uint32_t tx) {
  asm volatile(
      "{\n.reg .pred p;\n"
      "setp.ne.b32 p, %1, 0;\n"
      "@p mbarrier.arrive.expect_tx.shared::cta.b64 _, [%0], %1;\n}" ::"r"(C.b0 + 16 * S), "r"(tx) : "memory");
  asm volatile(
      "{\n.reg .pred p;\n"
      "setp.eq.b32 p, %0, %2;\n"
      "@p mbarrier.arrive.shared::cluster.b64 _, [%1];\n}" ::"r"(me), "r"(C.ra), "n"(S) : "memory");
}
template <int SYNC, int ID0, int ID1>
__device__ __forceinline__ void bar(uint32_t wg) {
  if (SYNC) asm volatile("{\n.reg .pred p;\nsetp.ne.b32 p, %0, 0;\n@!p bar.sync %1, 256;\n@p bar.sync %2, 256;\n}" ::"r"(wg), "n"(ID0), "n"(ID1) : "memory");
  else asm volatile("{\n.reg .pred p;\nsetp.ne.b32 p, %0, 0;\n@!p bar.arrive %1, 256;\n@p bar.arrive %2, 256;\n}" ::"r"(wg), "n"(ID0), "n"(ID1) : "memory");
}
__device__ __forceinline__ void sent(Ctx& C) { bar<0, 1, 2>(C.wg); }
__device__ __forceinline__ void await_sent(Ctx& C) { bar<1, 2, 1>(C.wg); }
__device__ __forceinline__ void sent2(Ctx& C) { bar<0, 10, 11>(C.wg); }
__device__ __forceinline__ void await_sent2(Ctx& C) { bar<1, 11, 10>(C.wg); }
__device__ __forceinline__ void await_taken(Ctx& C) { bar<1, 3, 4>(C.wg); }
__device__ __forceinline__ void taken(Ctx& C, uint32_t x) { if ((x & blockIdx.y) == 0) bar<0, 4, 3>(C.wg); }

__host__ __device__ constexpr int xoff(int u, int h) { return u * TUNIT + h * 2048; }
template <int B, int OF>
__device__ __forceinline__ void send(const Acc& A, uint32_t addr) {
  asm volatile("st.shared.v4.u32 [%4 + %5], {%0,%1,%2,%3};" ::"r"(A[4 * B]), "r"(A[4 * B + 1]), "r"(A[4 * B + 2]), "r"(A[4 * B + 3]), "r"(addr), "n"(OF) : "memory");
}
template <int B, int OF>
__device__ __forceinline__ void recv(Acc& A, uint32_t addr, bool on) {
  asm volatile("{\n.reg .pred p;\nsetp.ne.b32 p, %6, 0;\n@p ld.shared.v4.u32 {%0,%1,%2,%3}, [%4 + %5];\n}"
               : "+r"(A[4 * B]), "+r"(A[4 * B + 1]), "+r"(A[4 * B + 2]), "+r"(A[4 * B + 3]) : "r"(addr), "n"(OF), "r"((uint32_t)on) : "memory");
}
template <int OF>
__device__ __forceinline__ void fetch4(uint32_t* w, uint32_t addr) {
  asm volatile("ld.shared.v4.u32 {%0,%1,%2,%3}, [%4 + %5];" : "=r"(w[0]), "=r"(w[1]), "=r"(w[2]), "=r"(w[3]) : "r"(addr), "n"(OF) : "memory");
}
template <int I, int N>
__device__ __forceinline__ void add_to(Acc& A, const uint32_t* w, uint32_t sg) {
#pragma unroll
  for (int j = 0; j < N; j++) asm volatile("fma.rn.f16x2 %0, %1, %2, %0;" : "+r"(A[I + j]) : "r"(w[j]), "r"(sg));
}
template <int I, int N>
__device__ __forceinline__ void join(Acc& A, const Acc& B) {
#pragma unroll
  for (int j = I; j < I + N; j++) asm volatile("add.rn.f16x2 %0, %0, %1;" : "+r"(A[j]) : "r"(B[j]));
}
template <int B, int OF>
__device__ __forceinline__ void split(Acc& A, const Acc& Bb, uint32_t* w, uint32_t addr) {
#pragma unroll
  for (int j = 0; j < 4; j++)
    asm volatile("sub.rn.f16x2 %0, %1, %2;\nadd.rn.f16x2 %1, %1, %2;" : "=&r"(w[j]), "+r"(A[4 * B + j]) : "r"(Bb[4 * B + j]));
  asm volatile("st.shared.v4.u32 [%4 + %5], {%0,%1,%2,%3};" ::"r"(w[0]), "r"(w[1]), "r"(w[2]), "r"(w[3]), "r"(addr), "n"(OF) : "memory");
}
__host__ __device__ constexpr int pj(int k) { return 2 * (k >> 2) + (k & 1); }
__host__ __device__ constexpr int pp(int k) { return (k >> 1) & 1; }
template <int K>
__device__ __forceinline__ void rows(const Acc& P, Acc& Q, Acc& R, uint32_t* w) {
#pragma unroll
  for (int i = 0; i < 4; i++) {
    const int j = 8 * pj(K) + 2 * i + pp(K);
    asm volatile(
        "{\n.reg .b32 a, b;\n"
        "fma.rn.f16x2 a, %1, %4, %2;\n fma.rn.f16x2 b, %1, %5, %2;\n fma.rn.f16x2 %1, %1, %6, %2;\n"
        "fma.rn.f16x2 %0, %3, %7, a;\n fma.rn.f16x2 %2, %3, %8, b;\n add.rn.f16x2 %1, %1, %3;\n}"
        : "=r"(w[i]), "+r"(Q[j]), "+r"(R[j]) : "r"(P[j]), "r"(H_1_8), "r"(H_1_2), "r"(H_1_32), "r"(H_1_4), "r"(H_1_16));
  }
}
__device__ __forceinline__ uint32_t tobf(uint32_t h, uint32_t k) {
  uint32_t o;
  asm volatile("{\n.reg .b16 l, u;\n.reg .f32 a, b;\n.reg .b32 t;\nmov.b32 {l, u}, %1;\ncvt.f32.f16 a, l;\ncvt.f32.f16 b, u;\n"
               "cvt.rn.bf16x2.f32 t, b, a;\nmul.rn.bf16x2 %0, t, %2;\n}" : "=r"(o) : "r"(h), "r"(k));
  return o;
}
template <int K>
__device__ __forceinline__ void stg4(const char* o, const uint32_t* r) {
  asm volatile("st.global.cs.v4.u32 [%4 + %5], {%0,%1,%2,%3};" ::"r"(r[0]), "r"(r[1]), "r"(r[2]), "r"(r[3]), "l"(o), "n"(pp(K) * 8 * CH * 2 + pj(K) * 64) : "memory");
}
template <int K, int LAST = 0>
__device__ __forceinline__ void put(const Acc& A, Ctx& C) {
  uint32_t* w = C.w + (LAST ? 4 * (K & 1) : 8);
#pragma unroll
  for (int i = 0; i < 4; i++) w[i] = tobf(A[8 * pj(K) + 2 * i + pp(K)], C.k);
  stg4<K>(C.o, w);
}

constexpr uint64_t OUT_R = 0x252949290ull, OUT_S = 0x084210842108421ull, OUT_M = 0x151551540ull, OUT_F = 0x281015555ull;
constexpr int E0_AT = 6, E1_AT = 27;
__host__ __device__ constexpr int below(uint64_t m, int n) { return __builtin_popcountll(m & ((1ull << n) - 1)); }
static_assert(below(OUT_R, 36) == 12 && below(OUT_S, 60) == 12 && below(OUT_M, 35) == 12 && below(OUT_F, 36) == 12, "pieces");
static_assert(!(OUT_R & 15) && !(OUT_M & 0xC03F) && !(OUT_M & (OUT_M << 1)) && below(OUT_M, 8) <= 1 && below(OUT_M, 12) <= 4 && below(OUT_M, 24) <= 8 && below(OUT_M, 28) <= 9 && !(OUT_F & 0x7E000000) && E0_AT >= 6 && E1_AT >= 27, "order");

__host__ __device__ constexpr int r_out(int n) { return n >= 96 && n < 100 ? n - 96 : n == 124 || n == 125 ? n - 120 : -1; }
__host__ __device__ constexpr int d_out(int n) { return n >= 108 && n < 112 ? n - 108 : n == 122 || n == 123 ? n - 118 : -1; }
__host__ __device__ constexpr int r_in(int n) { return n >= 101 && n < 109 ? n - 101 : n == 130 || n == 131 ? n - 122 : n == 134 || n == 135 ? n - 124 : -1; }
__host__ __device__ constexpr int d_in(int n) { return n >= 112 && n < 120 ? n - 112 : n == 128 || n == 129 ? n - 120 : n == 132 || n == 133 ? n - 122 : -1; }
constexpr uint32_t XU_R = 0x750354, XU_D = 0x425421, XU_F = 0x984210;
template <int N, int FILL>
__device__ __forceinline__ void early(Acc& P, Acc& Q, Acc& R, Acc& S, Ctx& C) {
  if constexpr (FILL) {
    constexpr int I = N - 61;
    if constexpr (I == 0) await_sent(C);
    if constexpr (I >= 0 && I < 6) { fetch4<xoff(unit(XU_F, I), 0)>(C.w, C.xr); fetch4<xoff(unit(XU_F, I), 1)>(C.w + 4, C.xr); }
  } else {
    if constexpr (N == 101 || N == 116) await_sent(C);
    if constexpr (N == 112 || N == 128) await_sent2(C);
    if constexpr (r_in(N) >= 0) {
      constexpr int B = r_in(N);
      fetch4<xoff(unit(XU_R, B / 2), B & 1)>(C.w + 4, C.xr);
    }
    if constexpr (d_in(N) >= 0) recv<d_in(N), xoff(unit(XU_D, d_in(N) / 2), d_in(N) & 1)>(Q, C.xr, C.yes);
  }
}
template <int N, int FILL>
__device__ __forceinline__ void side(Acc& P, Acc& Q, Acc& R, Acc& S, Ctx& C) {
  const uint32_t te = C.sb + BAR_TEMPTY;
  if constexpr (FILL) {
    constexpr int I = N - 36, X = N - 54;
    if constexpr ((OUT_F >> I) & 1) { if (C.on) put<below(OUT_F, I)>(S, C); }
    if constexpr (X >= 0 && X < 6) { send<2 * X, xoff(unit(XU_F, X), 0)>(P, C.xs); send<2 * X + 1, xoff(unit(XU_F, X), 1)>(P, C.xs); }
    if constexpr (X == 5) sent(C);
    if constexpr (N == 66) { if (C.wg) asm volatile("bar.sync 6, 256;" ::: "memory"); }
    if constexpr (N == 71) { if (!C.wg) asm volatile("bar.arrive 6, 256;" ::: "memory"); }
    if constexpr (N >= 61 && N < 67) { if (C.yes) add_to<8 * (N - 61), 8>(P, C.w, C.sg); }
  } else if constexpr (N < 36) {
    if constexpr (N == 0) arrive(te + 16, C.one);
    if constexpr (N < 4) { if (C.on) join<12 * N, 12>(S, Q); }
    if constexpr ((OUT_R >> N) & 1) { if (C.on) put<below(OUT_R, N)>(R, C); }
    if constexpr (N == 30) arrive(te + 24, C.one);
  } else if constexpr (N < 96) {
    if constexpr ((OUT_S >> (N - 36)) & 1) { if (C.on) put<below(OUT_S, N - 36)>(S, C); }
    if constexpr (N == 48) arrive(te + 32, C.one);
    if constexpr (N == 72) arrive(te + 40, C.one);
  } else {
    constexpr int I = N - 108;
    if constexpr (I > 0) {
      if constexpr ((OUT_M >> (I - 1)) & 1) {
        if (C.yes) {
#pragma unroll
          for (int i = 0; i < 4; i++) C.w[8 + i] = tobf(C.w[i], C.k);
        }
        stg4<below(OUT_M, I - 1)>(C.o, C.w + 8);
      }
    }
    if constexpr (I >= 0) {
      if constexpr ((OUT_M >> I) & 1) { if (C.yes) rows<below(OUT_M, I)>(P, Q, R, C.w); }
    }
    if constexpr (N == 110 || N == 122) await_taken(C);
    if constexpr (r_out(N) >= 0) {
      constexpr int X = r_out(N);
      send<2 * X, xoff(unit(XU_R, X), 0)>(R, C.xs); send<2 * X + 1, xoff(unit(XU_R, X), 1)>(R, C.xs);
    }
    if constexpr (r_in(N) >= 0) {
      if (C.yes) {
        add_to<4 * r_in(N), 4>(R, C.w + 4, C.sg);
      }
    }
    if constexpr (d_out(N) >= 0) {
      constexpr int X = d_out(N);
      if (C.yes) { split<2 * X, xoff(unit(XU_D, X), 0)>(P, Q, C.w + 4, C.xs); split<2 * X + 1, xoff(unit(XU_D, X), 1)>(P, Q, C.w, C.xs); }
    }
    if constexpr (N == 99 || N == 111) sent(C);
    if constexpr (N == 109 || N == 125) sent2(C);
    if constexpr (N == 108) taken(C, R[31]);
    if constexpr (N == 120) taken(C, Q[11] | Q[15] | Q[19] | Q[23] | Q[27] | Q[31]);
    if constexpr (I == E0_AT) arrive(te, C.one && ((Q[3] | Q[7]) & blockIdx.y) == 0);
    if constexpr (I == E1_AT) arrive(te + 8, C.one && ((R[47] | Q[35] | Q[39] | Q[43] | Q[47]) & blockIdx.y) == 0);
  }
}
template <int W, int LEAD, int N0, int FILL, int J = 0>
__device__ __forceinline__ void group(Acc& P, Acc& Q, Acc& R, Acc& S, Ctx& C, uint64_t a) {
  constexpr int N = N0 + J;
  if (!C.ok) mbar_wait(C.b0 + 16 * (N % NUST), (N / NUST) & 1);
  wg_fence();
  wgmma192<LEAD && J == 0>(W == 0 ? P : W == 1 ? Q : W == 2 ? R : S, a + (((J / 3) * 2 * TCOL + (J % 3) * 16) >> 4), C.bd + (N % NUST) * (UTILE >> 4), blockIdx.y);
  wg_commit();
  C.ok = mbar_try(C.b0 + 16 * ((N + 1) % NUST), ((N + 1) / NUST) & 1);
  early<N, FILL>(P, Q, R, S, C);
  wg_wait<1>();
  release<(N + NUST - 1) % NUST>(C, N || C.on ? C.me : 0, N || C.on ? C.tx : 0);
  side<N, FILL>(P, Q, R, S, C);
  if constexpr (J < 5) group<W, LEAD, N0, FILL, J + 1>(P, Q, R, S, C, a);
}

__device__ __forceinline__ void fetch(const CUtensorMap* map, uint32_t bytes, uint32_t dst, uint32_t bar, int c, int x, int y, uint64_t pol) {
  asm volatile("{\n.reg .pred p;\nelect.sync _|p, 0xffffffff;\n"
               "@p mbarrier.arrive.expect_tx.shared::cta.b64 _, [%2], %6;\n"
               "@p cp.async.bulk.tensor.3d.shared::cluster.global.mbarrier::complete_tx::bytes.L2::cache_hint [%0], [%1, {%3,%4,%5}], [%2], %7;\n}"
               ::"r"(dst), "l"(map), "r"(bar), "r"(c), "r"(x), "r"(y), "r"(bytes), "l"(pol) : "memory");
}
constexpr uint64_t POL_FIRST = 0x12F0000000000000ull, POL_SAME = 0x10F0000000000000ull;

struct Params { uint8_t* U; uint32_t* ready; int lg, ufirst, ustep, nunit, umax, nfill, s0, second, nfirst; uint4 un[12]; };

__global__ void __launch_bounds__(NTHREADS, 1) wino_main(const __grid_constant__ CUtensorMap xmap8, const __grid_constant__ CUtensorMap xmap4,
                                                         const __grid_constant__ CUtensorMap xmap1, const __grid_constant__ CUtensorMap xmap0,
                                                         const __nv_bfloat16* __restrict__ xin, const __nv_bfloat16* __restrict__ wgt,
                                                         __nv_bfloat16* __restrict__ out, const Params P) {
  extern __shared__ __align__(1024) uint8_t smem[];
  { const uint32_t l = threadIdx.x * gridDim.x + blockIdx.x; if (l < 9 * CH * CH * 2 / 128) asm volatile("prefetch.global.L2 [%0];" ::"l"((const char*)wgt + l * 128u)); }
  const uint32_t sb = smem_u32(smem);
  const int warp = __shfl_sync(0xffffffffu, threadIdx.x >> 5, 0), lane = threadIdx.x & 31;
  const uint32_t cm = (1u << P.lg) - 1, rank = blockIdx.x & cm;
  const int cl = blockIdx.x >> P.lg;
  if (P.nfill == 0) {
    asm volatile("griddepcontrol.wait;" ::: "memory");
    *P.ready = 0;
    return;
  }
  const int nit = min(P.umax, (P.nunit - cl * P.ufirst + P.ustep - 1) / P.ustep), fu = cl % P.nfill;
  auto first = [&](int i) {
    const int u = cl * P.ufirst + i * P.ustep, q = (u * (205 << (P.lg - 1))) >> 12;
    const int st = P.s0 + (i < nit ? q : fu >> (3 - P.lg));
    const int y = i < nit ? ((u - q * (40 >> P.lg)) * 6 << P.lg) + 6 * rank : 240 + ((fu & ((8 >> P.lg) - 1)) * 2 << P.lg) + 2 * rank;
    return (st & 7) * 64 + ((st >> 3) * 256 + y) * IMG;
  };

  auto origin = [&](int i) { int o; asm volatile("ld.shared.u32 %0, [%1];" : "=r"(o) : "r"(sb + SM_ORG + 4 * i)); return o; };
  if (warp == 11 && lane < 7) sts(sb + SM_ORG + 4 * lane, (uint32_t)first(min(lane, nit)));

  if (warp != 11) asm volatile("barrier.cluster.arrive.relaxed.aligned;" ::: "memory");
  if (warp == 10) {
    sts(sb + SM_EXP, min(sample_exp((const char*)wgt + lane * (4 * 5168), 5168), 240u));
    asm volatile("bar.arrive 11, 288;" ::: "memory");
  }
  if (warp == 9) {
    const uint32_t e = sample_exp((const char*)xin + ((uint32_t)(first(0) + 2 * lane + (lane & 1) * IMG) * (CH * 2u) + lane % 6 * 64), CH / 2 + 16);
    sts(sb + SM_EXP + 4, e ? min(e, 138u) : 120);
    asm volatile("bar.arrive 12, 192;\nbar.arrive 13, 288;" ::: "memory");
  }
  if (warp < 8) {
    const int t0 = warp * gridDim.x + blockIdx.x;
    if (P.second || t0 >= NFILT) { cluster_wait(); asm volatile("bar.sync 11, 288;" ::: "memory"); }
    if (!P.second) {
      bool ok = true;
      if (t0 >= NFILT) made(P.ready, 1);
#pragma unroll 1
      for (int t = t0; t < NFILT; t += 8 * gridDim.x) ok = filter_task(wgt, P.U, t, lane, sb + SM_EXP, t == t0, t + 8 * gridDim.x >= NFILT, P.ready) && ok;
      if (!ok) atomicOr(P.ready, 1u << 31);
      made(P.ready, 1024);
    }
  }
  if (warp == 8) {
    uint32_t v; asm volatile("ld.volatile.global.u32 %0, [%1];" : "=r"(v) : "l"(P.ready) : "memory");
    if (v < P.nfirst) __nanosleep(100);
  }
  if (threadIdx.x == 352) {
    for (int i = 0; i < 2 * NUST; i++) { mbar_init(sb + BAR_U + 16 * i, 1); mbar_init(sb + BAR_U + 16 * i + 8, cm + 1); }
    for (int i = 0; i < 6; i++) { mbar_init(sb + BAR_TFULL + 8 * i, 5); mbar_init(sb + BAR_TEMPTY + 8 * i, 8); }
    sts(sb + SM_FLAG, 0u);
    asm volatile("fence.mbarrier_init.release.cluster;" ::: "memory");
    for (int i = 0; i < 2 * NUST; i++) mbar_expect_tx(sb + BAR_U + 16 * i, UTILE);
  }
  const uint32_t rbar = __shfl_sync(0xffffffffu, sb + BAR_RFULL + (warp & 3) * 16, 0), rbuf = sb + SM_R + (warp & 3) * (2 * RSLOT);
  if (warp >= 12) {
    if (lane == 0) {
      mbar_init(rbar, 1); mbar_init(rbar + 8, 1);
      asm volatile("fence.mbarrier_init.release.cluster;" ::: "memory");
    }
    __syncwarp();
    if (!P.second) __nanosleep(300);
    const int o = first(0);
#pragma unroll
    for (int i = 0; i < 2; i++)
      fetch(nit ? &xmap0 : &xmap4, nit ? RSLOT : RSLOT / 2, rbuf + i * RSLOT, rbar + 8 * i, 0, (o & 511) - 1 + (warp & 3) * 16 + i * 4, (o >> 9) - 1, POL_SAME);
  }
  __syncwarp();
  if (warp == 11) asm volatile("barrier.cluster.arrive.relaxed.aligned;" ::: "memory");
  if (warp == 8 || warp > 10) cluster_wait();
  if (warp > 10) asm volatile("bar.sync 12, 192;" ::: "memory");
  if (warp < 8) asm volatile("bar.sync 13, 288;" ::: "memory");
  uint2 ex;
  lds(ex, sb + SM_EXP);
  const uint32_t kin = h2((139 - ex.y) << 7);

  if (warp >= 12) {
    asm volatile("setmaxnreg.dec.sync.aligned.u32 40;");
    const int wi = warp - 12;
    const uint32_t tb = __shfl_sync(0xffffffffu, sb + SM_T + ((lane >> 1) & 3) * TCOL + (wi * 16 + (lane >> 3)) * 16 + (lane & 1) * 8, lane);
    const uint32_t src = rbuf + __shfl_sync(0xffffffffu, lane * 8, lane);
    const uint32_t nb = __shfl_sync(0xffffffffu, lane & blockIdx.y, lane);
    int o = origin(0), x = (o & 511) - 1 + wi * 16, y = (o >> 9) - 1;
    uint32_t m = 0;
    auto chunk = [&](auto fill, int i, uint32_t c, int xn, int yn) {
      constexpr int NR = fill.value ? 4 : 8;
      const CUtensorMap* const map = fill.value ? &xmap4 : &xmap8;
      const uint4 un = P.un[6 * fill.value + c];
      const bool turn = c == 5, half = fill.value || (turn && i + 1 == nit);
      const CUtensorMap* const map1 = half ? &xmap4 : &xmap8;
      const int c1 = turn ? 0 : c * 32 + 32, x1 = turn ? xn : x, y1 = turn ? yn : y;
      const uint32_t n1 = half ? RSLOT / 2 : RSLOT;
#pragma unroll
      for (int q = 0; q < 4; q++) {
        const uint32_t sl = (q & 1) * RSLOT, rb = rbar + (q & 1) * 8;
        uint2 d[8];
        mbar_wait_sleep(rb, q >> 1);
#pragma unroll
        for (int r = 0; r < NR; r++) lds(d[r], src + sl + r * RROW);
#pragma unroll
        for (int r = 0; r < NR; r++) scale(d[r], kin, m);
        if (q < 2) fetch(!fill.value && i + c == 0 ? &xmap0 : map, NR * RROW | (m & nb), rbuf + sl, rb, c * 32, x + 8 + 4 * q, y, c & 1 ? POL_FIRST : POL_SAME);
        else if (!fill.value || !turn) fetch(map1, n1 | (m & nb), rbuf + sl, rb, c1, x1 + 4 * q - 8, y1, c & 1 ? POL_SAME : POL_FIRST);
#pragma unroll
        for (int r = 0; r < NR; r++) tohalf(d[r]);
        if (q == 0 && (!fill.value || c < 3)) mbar_wait_sleep(sb + BAR_TEMPTY + 8 * c, (i & 1) ^ (c < 2));
        if (q == 0 && wi == 0) TRACE(2, tn);
        const uint32_t t = tb + 64 * q;
        if (fill.value) planes4(d, t + un.x, t + un.y);
        else planes8(d, t + un.x, t + un.y, t + un.z, t + un.w);
      }
      if (turn) {
        if (out_of_range(m)) asm volatile("red.shared.or.b32 [%0], %1;" ::"r"(sb + SM_FLAG), "r"(1u << i) : "memory");
        m = 0; x = xn; y = yn;
      }
      asm volatile("fence.proxy.async.shared::cta;" ::: "memory");
      __syncwarp();
      arrive_elect(sb + BAR_TFULL + 8 * c);
    };
#pragma unroll 1
    for (int i = 0; i < nit; i++) {
      o = origin(i + 1);
#pragma unroll 1
      for (uint32_t c = 0; c < 6; c++) chunk(std::false_type(), i, c, (o & 511) - 1 + wi * 16, (o >> 9) - 1);
    }
#pragma unroll 1
    for (uint32_t c = 0; c < 6; c++) chunk(std::true_type(), nit, c, 0, 0);
    cluster_sync();
  } else if (warp >= 8) {
    asm volatile("setmaxnreg.dec.sync.aligned.u32 24;");
    if (warp < 10) {
      const uint32_t g = warp - 8, s0 = rank ^ (5 * g & cm);
      const uint32_t ring = sb + SM_U + g * (NUST * UTILE), ub = sb + BAR_U + g * (NUST * 16);
      if (warp == 8) {
        uint32_t v, i = 0;
        do { asm volatile("ld.acquire.gpu.global.u32 %0, [%1];" : "=r"(v) : "l"(P.ready) : "memory"); if (++i > 5000000u) __trap(); } while ((v & 1023) < P.nfirst);
        asm volatile("bar.arrive 7, 64;" ::: "memory");
      }
      asm volatile("bar.sync 9, 64;" ::: "memory");
      asm volatile("fence.proxy.async.global;" ::: "memory");
      uint32_t ph = 1;
#pragma unroll 1
      for (int i = 0; i <= nit; i++) {
        const uint8_t* from = P.U + g * UWG + (i < nit ? 0 : NROUND * NUST * UTILE);
#pragma unroll 1
        for (uint32_t t = 0; t < (i < nit ? NROUND : NFROUND); t++, ph ^= 1, from += NUST * UTILE) {
          if (i == 0 && t == 36 / NUST) asm volatile("bar.sync 8, 96;\nfence.proxy.async.global;" ::: "memory");
#pragma unroll 1
          for (uint32_t s = s0; s < 8 || (s < 16 && s0 == (4 & cm)); s = s + cm + 1 < 8 ? s + cm + 1 : s < 8 ? 8 : 16) {
            mbar_wait(ub + 16 * s + 8, ph);
            asm volatile(
                "{\n.reg .pred p;\n"
                "elect.sync _|p, 0xffffffff;\n"
                "@p cp.async.bulk.shared::cluster.global.mbarrier::complete_tx::bytes.multicast::cluster [%0], [%1], %2, [%4], %3;\n}"
                ::"r"(ring + s * UTILE), "l"(from + s * UTILE), "n"(UTILE), "h"((uint16_t)((2u << cm) - 1)), "r"(ub + 16 * s) : "memory");
          }
        }
      }
    } else if (warp == 10) {
      uint32_t v, i = 0;
      do { asm volatile("ld.acquire.gpu.global.u32 %0, [%1];" : "=r"(v) : "l"(P.ready) : "memory"); if (++i > 5000000u) __trap(); } while (((v >> 10) & 1023) < P.nfirst);
      if (v >> 31) asm volatile("red.shared.or.b32 [%0], %1;" ::"r"(sb + SM_FLAG), "r"(0xFFFFu) : "memory");
      __syncwarp();
      asm volatile("bar.arrive 8, 96;" ::: "memory");
      asm volatile("bar.sync 7, 64;" ::: "memory");
      if (P.second && lane == 0 && ((atomicAdd(P.ready, 1 << 20) >> 20) & 1023) == gridDim.x - 1) *P.ready = 0;
      asm volatile("griddepcontrol.launch_dependents;");
      auto ahead = [&](int i, uint32_t sl, int r) {
        const int o = origin(i), nr = i < nit ? 6 : 2;
        auto row = [&](int y) {
          asm volatile("{\n.reg .pred p;\nelect.sync _|p, 0xffffffff;\n@p cp.async.bulk.prefetch.tensor.3d.L2.global [%0, {%1,%2,%3}];\n}"
                       ::"l"(&xmap1), "r"(sl * 64), "r"((o & 511) - 1), "r"((o >> 9) + y) : "memory");
        };
        if (r < nr) row(r);
        if (r == 0 && rank == 0) row(-1);
        if (r + 1 == nr && rank == cm) row(nr);
      };
      uint32_t ph = 0;
#pragma unroll 1
      for (int i = 0; i <= nit; i++) {
#pragma unroll 1
        for (uint32_t t = 0; t < (i < nit ? NROUND : NFROUND - 3); t++, ph ^= 1) {
#pragma unroll 1
          for (int n = P.second ? 400 : 20; n && !mbar_try(sb + BAR_U + 16 * rank, ph); n--) __nanosleep(100);
          if (t - 1 < 6) ahead(i, 2, t - 1);
          if (i < nit && t - 6 < 6) ahead(i + 1, 0, t - 6);
          if (i < nit && t - 10 < 6) ahead(i + 1, 1, t - 10);
          if (((cl + t) & 7) == 0 && !P.second) {
            const uint32_t r = i == nit ? NROUND + t + 3 : t + 3 < NROUND || i + 1 == nit ? t + 3 : t + 3 - NROUND;
            if (lane < (rank == 4 ? 4 : 2))
              asm volatile("cp.async.bulk.prefetch.L2.global [%0], %1;" ::"l"(P.U + ((lane & 1) * UWG + (r * NUST + (lane >> 1 ? 8 : rank)) * UTILE)), "n"(UTILE) : "memory");
            __syncwarp();
          }
        }
      }
    } else {
      const uint32_t tb = sb + SM_T + ((lane >> 2) & 3) * TCOL + (64 + (lane >> 4)) * 16 + (lane & 3) * 4;
      uint32_t iph = 0;
#pragma unroll 1
      for (int i = 0; i <= nit; i++, iph ^= 1) {
        const int o = origin(i), x = (o & 511) + 63 + (lane >> 4), y = (o >> 9) - 1, nr = i < nit ? 8 : 4;
        const char* p = (const char*)xin + (uint32_t)(o + 63 + (lane >> 4)) * (CH * 2u) + (lane & 15) * 4;
        uint32_t m = 0;
#pragma unroll 1
        for (uint32_t c = 0; c < 6; c++, p += 64) {
          uint32_t d[8];
#pragma unroll
          for (int r = 0; r < 8; r++) {
            d[r] = 0;
            if (x < IMG && (uint32_t)(y + r) < IMG && r < nr) asm volatile("ld.global.nc.u32 %0, [%1];" : "=r"(d[r]) : "l"(p + (r - 1) * ROWB));
          }
#pragma unroll
          for (int r = 0; r < 8; r++) { scale(d[r], kin, m); tohalf(d[r]); }
          if (i < nit || c < 3) mbar_wait_sleep(sb + BAR_TEMPTY + 8 * c, iph ^ (c < 2));
          if (i < nit) planes8(d, tb + unit(UN_P, c) * TUNIT, tb + unit(UN_Q, c) * TUNIT, tb + unit(UN_R, c) * TUNIT, tb + unit(UN_S, c) * TUNIT);
          else planes4(d, tb + unit(UN_FP, c) * TUNIT, tb + unit(UN_FQ, c) * TUNIT);
          if (c == 5 && (m & 0x78007800u)) asm volatile("red.shared.or.b32 [%0], %1;" ::"r"(sb + SM_FLAG), "r"(1u << i) : "memory");
          asm volatile("fence.proxy.async.shared::cta;" ::: "memory");
          __syncwarp();
          arrive_elect(sb + BAR_TFULL + 8 * c);
        }
      }
      if (P.second == 2) asm volatile("griddepcontrol.wait;" ::: "memory");
    }
    __syncwarp();
    cluster_sync();
  } else {
    const uint32_t ek = ex.x ? ex.x + ex.y - 119 : 0;
    asm volatile("setmaxnreg.inc.sync.aligned.u32 224;");
    const int wg = warp >> 2;
    Ctx C;
    C.sb = sb; C.wg = wg;
    C.b0 = sb + BAR_U + wg * (NUST * 16);
    C.bd = desc(BLO + (((sb + SM_U + wg * (NUST * UTILE)) & 0x3FFFF) >> 4), BHI);
    C.ad = desc(ALO + (((sb + SM_T + wg * TWG) & 0x3FFFF) >> 4), AHI);
    C.me = __shfl_sync(0xffffffffu, threadIdx.x & 127, lane); C.tx = __shfl_sync(0xffffffffu, (threadIdx.x & 127) == 0 ? UTILE : 0, lane);
    asm volatile("mapa.shared::cluster.u32 %0, %1, %2;" : "=r"(C.ra) : "r"(C.b0 + 16 * lane + 8), "r"(((lane == 8 ? 4 : lane) ^ 5 * wg) & cm));
    C.ok = 0;
    const uint32_t t16 = __shfl_sync(0xffffffffu, (warp & 3) * 512 + lane * 16, lane);
    C.one = (t16 & 511) == 0;
    C.xs = sb + SM_T + wg * TWG + t16;
    C.xr = sb + SM_T + (wg ^ 1) * TWG + t16;
    C.k = h2(ek << 7); C.sg = wg ? H_1 : H_N1;
    C.yes = C.sb != gridDim.x;
    const int drow = wg ? -2 * ROWB : 2 * ROWB;
    const char* const ob = (const char*)out + (uint32_t)(((warp & 3) * 16 + (lane >> 2)) * CH + (lane & 3) * 8) * 2u;
    C.o = ob;
#pragma unroll
    for (int i = 0; i < 12; i++) C.w[i] = 0;

    Acc A0, A1, A2, A3;
#pragma unroll
    for (int j = 0; j < 48; j++) { A0[j] = 0; A1[j] = 0; A2[j] = 0; A3[j] = 0; }
#define G(W, LEAD, N0, FILL, U) group<W, LEAD, N0, FILL>(A0, A1, A2, A3, C, C.ad + (U) * (TUNIT >> 4))
    uint32_t ph = 0;
#pragma unroll 1
    for (int item = 0;; item++) {
      C.on = item != 0;
      if (P.second && item == 2) {
        const int wait = (5 - nit) * 28000 - 10000;
        uint32_t c0, c;
        asm volatile("mov.u32 %0, %%clock;" : "=r"(c0));
        do { __nanosleep(500); asm volatile("mov.u32 %0, %%clock;" : "=r"(c)); } while ((int)(c - c0) < wait);
      }
      C.ad += item & blockIdx.y; C.bd += item & blockIdx.y;
      mbar_wait(sb + BAR_TFULL, ph);
      G(0, 1, 0, 0, unit(UN_P, 0));
      G(1, 1, 6, 0, unit(UN_Q, 0));
      mbar_wait(sb + BAR_TFULL + 8, ph);
      G(0, 0, 12, 0, unit(UN_P, 1)); G(1, 0, 18, 0, unit(UN_Q, 1));
      mbar_wait(sb + BAR_TFULL + 16, ph);
      G(0, 0, 24, 0, unit(UN_P, 2)); G(1, 0, 30, 0, unit(UN_Q, 2));
      C.o -= 2 * drow;
      if (item == nit) break;
      G(2, 1, 36, 0, unit(UN_R, 0)); G(2, 0, 42, 0, unit(UN_R, 1)); G(2, 0, 48, 0, unit(UN_R, 2));
      mbar_wait(sb + BAR_TFULL + 24, ph);
      G(2, 0, 54, 0, unit(UN_R, 3)); G(0, 0, 60, 0, unit(UN_P, 3)); G(1, 0, 66, 0, unit(UN_Q, 3));
      mbar_wait(sb + BAR_TFULL + 32, ph);
      G(2, 0, 72, 0, unit(UN_R, 4)); G(0, 0, 78, 0, unit(UN_P, 4)); G(1, 0, 84, 0, unit(UN_Q, 4));
      mbar_wait(sb + BAR_TFULL + 40, ph);
      G(2, 0, 90, 0, unit(UN_R, 5)); G(0, 0, 96, 0, unit(UN_P, 5)); G(1, 0, 102, 0, unit(UN_Q, 5));
      ph ^= 1;
      C.o = ob + (uint32_t)(origin(item) + (2 + wg) * IMG) * (CH * 2u);
      G(3, 1, 108, 0, unit(UN_S, 0)); G(3, 0, 114, 0, unit(UN_S, 1)); G(3, 0, 120, 0, unit(UN_S, 2));
      G(3, 0, 126, 0, unit(UN_S, 3)); G(3, 0, 132, 0, unit(UN_S, 4)); G(3, 0, 138, 0, unit(UN_S, 5));
      C.o += drow;
    }
    mbar_wait(sb + BAR_TFULL + 24, ph);
    G(0, 0, 36, 1, unit(UN_FP, 3));
    mbar_wait(sb + BAR_TFULL + 32, ph);
    G(0, 0, 42, 1, unit(UN_FP, 4));
    mbar_wait(sb + BAR_TFULL + 40, ph);
    G(0, 0, 48, 1, unit(UN_FP, 5));
    G(1, 0, 54, 1, unit(UN_FQ, 3)); G(1, 0, 60, 1, unit(UN_FQ, 4)); G(1, 0, 66, 1, unit(UN_FQ, 5));
#undef G
    wg_wait<0>();
    uint32_t redo;
    asm volatile("ld.shared.u32 %0, [%1];" : "=r"(redo) : "r"(sb + SM_FLAG) : "memory");
    if (cl < P.nfill) {
      C.o = ob + (uint32_t)(origin(nit) + wg * IMG) * (CH * 2u);
      join<0, 48>(A1, A0);
      put<0, 1>(A1, C); put<1, 1>(A1, C); put<2, 1>(A1, C); put<3, 1>(A1, C); put<4, 1>(A1, C); put<5, 1>(A1, C);
      put<6, 1>(A1, C); put<7, 1>(A1, C); put<8, 1>(A1, C); put<9, 1>(A1, C); put<10, 1>(A1, C); put<11, 1>(A1, C);
    }
    if (ek - 1 > 253) redo = 0xFFFF;
    if (redo) {
      asm volatile("bar.sync 5, 256;" ::: "memory");
      const int k = threadIdx.x;
#pragma unroll 1
      for (int i = 0; i < nit + (cl < P.nfill); i++) {
        if (!((redo >> i) & 1) || k >= CH) continue;
        const int o = origin(i);
#pragma unroll 1
        for (int t = 0; t < (i < nit ? 48 : 16); t++) {
          const int y = (o >> 9) + (t >> 3), x = (o & 511) + (t & 7) * 8;
          float acc[8];
#pragma unroll
          for (int j = 0; j < 8; j++) acc[j] = 0.f;
#pragma unroll 1
          for (int rs = 0; rs < 9; rs++) {
            const int yy = y + rs / 3 - 1, xx = x + rs % 3 - 1;
            if ((uint32_t)yy >= IMG) continue;
#pragma unroll 1
            for (int c = 0; c < CH; c += 2) {
              const float w0 = __bfloat162float(wgt[(rs * CH + c) * CH + k]), w1 = __bfloat162float(wgt[(rs * CH + c + 1) * CH + k]);
#pragma unroll
              for (int j = 0; j < 8; j++) {
                if ((uint32_t)(xx + j) < IMG) {
                  const uint32_t v = __ldg(reinterpret_cast<const uint32_t*>(xin + (yy * IMG + xx + j) * CH + c));
                  acc[j] = fmaf(__uint_as_float(v & 0xFFFF0000u), w1, fmaf(__uint_as_float(v << 16), w0, acc[j]));
                }
              }
            }
          }
#pragma unroll
          for (int j = 0; j < 8; j++) out[(y * IMG + x + j) * CH + k] = __float2bfloat16(acc[j]);
        }
      }
    }
    __syncwarp();
    cluster_sync();
  }
}

typedef CUresult (*EncFn)(CUtensorMap*, CUtensorMapDataType, cuuint32_t, void*, const cuuint64_t*, const cuuint64_t*,
                          const cuuint32_t*, const cuuint32_t*, CUtensorMapInterleave, CUtensorMapSwizzle,
                          CUtensorMapL2promotion, CUtensorMapFloatOOBfill);

}

extern "C" void kernel_launch(void* const* d_in, const int* in_sizes, int n_in, void* d_out, int out_size) {
  const __nv_bfloat16* x = (const __nv_bfloat16*)d_in[0];
  const __nv_bfloat16* w = (const __nv_bfloat16*)d_in[1];
  __nv_bfloat16* out = (__nv_bfloat16*)d_out;

  static EncFn enc = nullptr;
  static void *U = nullptr, *ready = nullptr;
  if (!enc) {
    cudaGetSymbolAddress(&U, g_U);
    cudaGetSymbolAddress(&ready, g_ready);
    void* fn = nullptr; cudaDriverEntryPointQueryResult st;
    cudaGetDriverEntryPoint("cuTensorMapEncodeTiled", &fn, cudaEnableDefault, &st);
    enc = (EncFn)fn;
    cudaFuncSetAttribute(wino_main, cudaFuncAttributeMaxDynamicSharedMemorySize, SMEM_BYTES);
  }
  CUtensorMap xmap[4];
  for (int i = 0; i < 4; i++) {
    cuuint64_t dims[3] = {CH, IMG, IMG};
    cuuint64_t str[2] = {CH * 2, (cuuint64_t)ROWB};
    cuuint32_t box[3] = {i != 2 ? 32u : 64u, i != 2 ? 4u : 66u, i == 2 ? 1u : i == 1 ? 4u : 8u};
    cuuint32_t es[3] = {1, 1, 1};
    enc(&xmap[i], CU_TENSOR_MAP_DATA_TYPE_BFLOAT16, 3, (void*)x, dims, str, box, es, CU_TENSOR_MAP_INTERLEAVE_NONE,
        CU_TENSOR_MAP_SWIZZLE_NONE, i == 3 ? CU_TENSOR_MAP_L2_PROMOTION_NONE : CU_TENSOR_MAP_L2_PROMOTION_L2_128B, CU_TENSOR_MAP_FLOAT_OOB_FILL_NONE);
  }
  cudaLaunchConfig_t cfg = {};
  cudaLaunchAttribute attr[2];
  cfg.blockDim = dim3(NTHREADS);
  cfg.dynamicSmemBytes = SMEM_BYTES;
  cfg.stream = cudaStreamPerThread;
  attr[0].id = cudaLaunchAttributeClusterDimension;
  attr[0].val.clusterDim.x = 1 << LGA; attr[0].val.clusterDim.y = 1; attr[0].val.clusterDim.z = 1;
  attr[1].id = cudaLaunchAttributeProgrammaticStreamSerialization;
  attr[1].val.programmaticStreamSerializationAllowed = 1;
  cfg.attrs = attr;
  static int nca = 0, ncb = 0;
  if (!nca) {
    int n = 0, n2 = 0;
    cfg.numAttrs = 1;
    cfg.gridDim = dim3(128);
    cudaOccupancyMaxActiveClusters(&n, wino_main, &cfg);
    attr[0].val.clusterDim.x = 2;
    cudaOccupancyMaxActiveClusters(&n2, wino_main, &cfg);
    attr[0].val.clusterDim.x = 1 << LGA;
    nca = n < 1 ? 1 : n > 16 ? 16 : n;
    ncb = n2 - (nca << LGA) / 2;
  }
  cfg.numAttrs = 1;
  cfg.gridDim = dim3(nca << LGA);
  Params P = {(uint8_t*)U, (uint32_t*)ready, LGA, 5, 1, 5 * nca, 5, nca, 0, 0, nca << LGA};
  for (int c = 0; c < 6; c++) {
    P.un[c] = make_uint4(unit(UN_P, c) * TUNIT, unit(UN_Q, c) * TUNIT, unit(UN_R, c) * TUNIT, unit(UN_S, c) * TUNIT);
    P.un[6 + c] = make_uint4(unit(UN_FP, c) * TUNIT, unit(UN_FQ, c) * TUNIT, 0, 0);
  }
  cudaLaunchKernelEx(&cfg, wino_main, xmap[0], xmap[1], xmap[2], xmap[3], x, w, out, P);
  const int nf = 4 * (16 - nca), nb = nf == 0 ? 1 : ncb < nf ? nf : ncb > 5 * nf ? 5 * nf : ncb;
  attr[0].val.clusterDim.x = 2;
  cfg.numAttrs = 2;
  cfg.gridDim = dim3(2 * nb);
  cudaStreamCaptureStatus cap = cudaStreamCaptureStatusNone;
  cudaStreamIsCapturing(cfg.stream, &cap);
  P.lg = 1; P.ufirst = 1; P.ustep = nb; P.nunit = 5 * nf; P.nfill = nf; P.s0 = nca; P.second = cap == cudaStreamCaptureStatusActive ? 1 : 2;
  cudaLaunchKernelEx(&cfg, wino_main, xmap[0], xmap[1], xmap[2], xmap[3], x, w, out, P);
}
```

```cpp
#include <cuda_runtime.h>
#include <cuda.h>
#include <cuda_bf16.h>
#include <stdint.h>
#include <type_traits>

namespace {
#define PAUSE_B 16000

constexpr int IMG = 512;
constexpr int CH = 192;
constexpr int ROWB = IMG * CH * 2;
constexpr int TCOL = 66 * 16;
constexpr int TUNIT = 4 * TCOL;
constexpr int TWG = 12 * TUNIT;
constexpr int RROW = 4 * 64;
constexpr int RSLOT = 8 * RROW;
constexpr int UTILE = 192 * 32;
constexpr int NUST = 9;
constexpr int NROUND = 144 / NUST, NFROUND = 72 / NUST;
constexpr int UWG = (NROUND + NFROUND) * NUST * UTILE;
constexpr int SM_U = 0;
constexpr int SM_R = SM_U + 2 * NUST * UTILE;
constexpr int SM_T = 131072 - 1024;
constexpr int SM_BAR = SM_T + 2 * TWG;
static_assert(SM_R + 4 * 2 * RSLOT <= SM_T, "smem");
constexpr int SMEM_BYTES = SM_BAR + 256 + 32 * NUST + 16;
constexpr int NTHREADS = 512;
constexpr uint32_t BAR_TFULL = SM_BAR, BAR_TEMPTY = SM_BAR + 48, SM_FLAG = SM_BAR + 96, SM_ORG = SM_BAR + 100, SM_EXP = SM_BAR + 256 + 32 * NUST, BAR_RFULL = SM_BAR + 128,
                   BAR_U = SM_BAR + 256;
static_assert(SMEM_BYTES <= 232448 && SM_R % 128 == 0, "smem");

__host__ __device__ constexpr int group_of(int q, int c) {
  return q == 0 ? (c < 3 ? 2 * c : 3 * c + 1) : q == 1 ? (c < 3 ? 2 * c + 1 : 3 * c + 2) : q == 2 ? (c < 3 ? 6 + c : 3 * c) : q == 3 ? 18 + c
       : q == 4 ? 24 + (c < 3 ? 2 * c : 3 + c) : 24 + (c < 3 ? 2 * c + 1 : 6 + c);
}
constexpr uint32_t UN_P = 0x141820, UN_Q = 0x252941, UN_R = 0x030A53, UN_S = 0xA98B76, UN_FP = 0xA53820, UN_FQ = 0xB76941;
__host__ __device__ constexpr uint32_t unit(uint32_t tab, int c) { return (tab >> (4 * c)) & 15; }

__device__ __align__(1024) uint8_t g_U[2 * UWG];
__device__ uint32_t g_ready[64];
#define TRACE(row, i)

__device__ __forceinline__ void cluster_wait() { asm volatile("barrier.cluster.wait.acquire.aligned;" ::: "memory"); }
__device__ __forceinline__ uint32_t sample_exp(const char* p, uint32_t stride) {
  uint32_t m = 0;
  uint4 v[4];
#pragma unroll
  for (int i = 0; i < 4; i++)
    asm volatile("ld.global.nc.v4.u32 {%0,%1,%2,%3}, [%4];" : "=r"(v[i].x), "=r"(v[i].y), "=r"(v[i].z), "=r"(v[i].w) : "l"(p + i * stride));
  cluster_wait();
#pragma unroll
  for (int i = 0; i < 4; i++)
    m = __vmaxu2(__vmaxu2(m, __vmaxu2(v[i].x & 0x7FFF7FFFu, v[i].y & 0x7FFF7FFFu)), __vmaxu2(v[i].z & 0x7FFF7FFFu, v[i].w & 0x7FFF7FFFu));
  return __reduce_max_sync(0xffffffffu, max(m & 0xFFFFu, m >> 16)) >> 7;
}

#define PQBITS 9
constexpr int NFILT = 2 * 6 * 24 * 3;
__device__ __forceinline__ void made(uint32_t* ready, uint32_t n) {
  asm volatile("fence.proxy.async.global;\nbar.sync 10, 256;" ::: "memory");
  if (threadIdx.x == 0) asm volatile("red.release.gpu.global.add.u32 [%0], %1;" ::"l"(ready), "r"(n) : "memory");
  __syncwarp();
}
__device__ __forceinline__ bool filter_task(const __nv_bfloat16* __restrict__ w, uint8_t* U, int t, int lane, uint32_t ew, bool first, bool last, uint32_t* ready) {
  const int wg = t & 1, blk = (t >> 1) % 6, co = (t / 12) % 24, s = t / (12 * 24);
  const int k = blk * 32 + ((lane >> 1) & 3) * 8 + (lane >> 3) * 2 + (lane & 1);
  const unsigned short* wp = reinterpret_cast<const unsigned short*>(w) + ((wg * 6 + s) * CH + co * 8) * CH + k;
  const int dr = wg ? -3 * CH * CH : 3 * CH * CH;
  uint32_t g[3][8];
#pragma unroll
  for (int r = 0; r < 3; r++)
#pragma unroll
    for (int i = 0; i < 8; i++) asm volatile("ld.global.nc.u16 %0, [%1];" : "=r"(g[r][i]) : "l"(wp + r * dr + i * CH));
  const int chunk = co >> 2;
  uint8_t* const u = U + wg * UWG + (3 * ((co >> 1) & 1) + s) * UTILE + (blk * 4 + (lane >> 3)) * 256 + (co & 1) * 128 + (lane & 7) * 16;
  if (first) { cluster_wait(); asm volatile("bar.sync 11, 288;" ::: "memory"); }
  asm volatile("ld.shared.u32 %0, [%0];" : "+r"(ew)::"memory");
  const float su = __uint_as_float((249 - ew) << 23), low = __uint_as_float(15u << 23);
  const float na = wg ? 128.f / 90.f : 1.f / 1.40625f, sg = wg ? -1.f : 1.f;
  float v[5][8], m = 0.f;
#pragma unroll
  for (int i = 0; i < 8; i++) {
    const float a = __uint_as_float(g[0][i] << 16) * su, b = __uint_as_float(g[1][i] << 16) * su, c = __uint_as_float(g[2][i] << 16) * su;
    asm("{\n.reg .f32 t;\nmax.NaN.f32 t, %1, %2;\nmax.NaN.f32 %0, %0, %3;\nmax.NaN.f32 %0, %0, t;\n}" : "+f"(m) : "f"(fabsf(a)), "f"(fabsf(b)), "f"(fabsf(c)));
    const float e = fmaf(0.25f, c, a) * na, o = b * (0.5f * na), d = fmaf(a + c, sg, b);
    v[0][i] = e + o; v[1][i] = (e - o) * sg; v[2][i] = d * (low / -4.5f); v[3][i] = a * (-sg * low); v[4][i] = d * (0.5f * low);
  }
#pragma unroll
  for (int q = 0; q < 5; q++) {
    uint32_t pk[4];
#pragma unroll
    for (int i = 0; i < 4; i++) {
      if (q < 2) {
        asm("cvt.rz.f16x2.f32 %0, %1, %2;" : "=r"(pk[i]) : "f"(v[q][2 * i + 1]), "f"(v[q][2 * i]));
        pk[i] = (pk[i] + (0x00010001u << (10 - PQBITS))) & ~((0x00010001u << (11 - PQBITS)) - 0x00010001u);
      } else {
        asm("cvt.rn.bf16x2.f32 %0, %1, %2;" : "=r"(pk[i]) : "f"(v[q][2 * i + 1]), "f"(v[q][2 * i]));
        pk[i] += (pk[i] & 0x7FFF7FFFu) * 7;
      }
    }
    *reinterpret_cast<uint4*>(u + 6 * group_of(q, chunk) * UTILE) = make_uint4(pk[0], pk[1], pk[2], pk[3]);
    if (q == 3) *reinterpret_cast<uint4*>(u + 6 * group_of(5, chunk) * UTILE) = make_uint4(pk[0], pk[1], pk[2], pk[3]);
    if (q == 1 && last) made(ready, 1);
  }
  return m < 0.1875f;
}

__device__ __forceinline__ uint32_t smem_u32(const void* p) { return (uint32_t)__cvta_generic_to_shared(p); }
__device__ __forceinline__ void mbar_init(uint32_t bar, uint32_t cnt) {
  asm volatile("mbarrier.init.shared::cta.b64 [%0], %1;" ::"r"(bar), "r"(cnt));
}
__device__ __forceinline__ void mbar_expect_tx(uint32_t bar, uint32_t bytes) {
  asm volatile("mbarrier.arrive.expect_tx.shared::cta.b64 _, [%0], %1;" ::"r"(bar), "r"(bytes) : "memory");
}
__device__ __forceinline__ void mbar_wait(uint32_t bar, uint32_t parity) {
  asm volatile(
      "{\n.reg .pred p;\n"
      "WAIT_%=:\n"
      "mbarrier.try_wait.parity.shared::cta.b64 p, [%0], %1;\n"
      "@p bra DONE_%=;\n"
      "bra WAIT_%=;\n"
      "DONE_%=:\n}" ::"r"(bar), "r"(parity) : "memory");
}
__device__ __forceinline__ uint32_t mbar_try(uint32_t bar, uint32_t parity) {
  uint32_t ok;
  asm volatile(
      "{\n.reg .pred p;\n"
      "mbarrier.test_wait.parity.shared::cta.b64 p, [%1], %2;\n"
      "selp.u32 %0, 1, 0, p;\n}" : "=r"(ok) : "r"(bar), "r"(parity) : "memory");
  return ok;
}
__device__ __forceinline__ void mbar_wait_sleep(uint32_t bar, uint32_t parity) {
  asm volatile(
      "{\n.reg .pred p;\n"
      "WAIT_%=:\n"
      "mbarrier.try_wait.parity.shared::cta.b64 p, [%0], %1, 20000;\n"
      "@p bra DONE_%=;\n"
      "bra WAIT_%=;\n"
      "DONE_%=:\n}" ::"r"(bar), "r"(parity) : "memory");
}
#undef mbar_wait
#undef mbar_wait_sleep
__device__ __forceinline__ void arrive_elect(uint32_t bar) {
  asm volatile(
      "{\n.reg .pred p;\n"
      "elect.sync _|p, 0xffffffff;\n"
      "@p mbarrier.arrive.shared::cta.b64 _, [%0];\n}" ::"r"(bar) : "memory");
}
__device__ __forceinline__ void cluster_sync() {
  asm volatile("barrier.cluster.arrive.relaxed.aligned;\nbarrier.cluster.wait.aligned;" ::: "memory");
}
__device__ __forceinline__ void wg_fence() { asm volatile("wgmma.fence.sync.aligned;" ::: "memory"); }
__device__ __forceinline__ void wg_commit() { asm volatile("wgmma.commit_group.sync.aligned;" ::: "memory"); }
template <int N> __device__ __forceinline__ void wg_wait() { asm volatile("wgmma.wait_group.sync.aligned %0;" ::"n"(N) : "memory"); }
template <int LEAD>
__device__ __forceinline__ void wgmma192(uint32_t (&d)[48], uint64_t adesc, uint64_t bdesc, uint32_t acc) {
  asm volatile(
      "{\n.reg .pred p;\n"
      "setp.ne.b32 p, %50, 0;\n"
      "wgmma.mma_async.sync.aligned.m64n192k16.f16.f16.f16 "
      "{%0,%1,%2,%3,%4,%5,%6,%7,%8,%9,%10,%11,%12,%13,%14,%15,%16,%17,%18,%19,%20,%21,%22,%23,%24,%25,%26,%27,%28,%29,%30,%31,%32,%33,%34,%35,%36,%37,%38,%39,%40,%41,%42,%43,%44,%45,%46,%47}, %48, %49, p, 1, 1, 0, 0;\n}\n"
      : "+r"(d[0]),"+r"(d[1]),"+r"(d[2]),"+r"(d[3]),"+r"(d[4]),"+r"(d[5]),"+r"(d[6]),"+r"(d[7]),"+r"(d[8]),"+r"(d[9]),"+r"(d[10]),"+r"(d[11]),"+r"(d[12]),"+r"(d[13]),"+r"(d[14]),"+r"(d[15]),"+r"(d[16]),"+r"(d[17]),"+r"(d[18]),"+r"(d[19]),"+r"(d[20]),"+r"(d[21]),"+r"(d[22]),"+r"(d[23]),"+r"(d[24]),"+r"(d[25]),"+r"(d[26]),"+r"(d[27]),"+r"(d[28]),"+r"(d[29]),"+r"(d[30]),"+r"(d[31]),"+r"(d[32]),"+r"(d[33]),"+r"(d[34]),"+r"(d[35]),"+r"(d[36]),"+r"(d[37]),"+r"(d[38]),"+r"(d[39]),"+r"(d[40]),"+r"(d[41]),"+r"(d[42]),"+r"(d[43]),"+r"(d[44]),"+r"(d[45]),"+r"(d[46]),"+r"(d[47])
      : "l"(adesc), "l"(bdesc), "r"(LEAD ? acc : 1u));
}

__device__ __forceinline__ void sts(uint32_t addr, uint32_t v) { asm volatile("st.shared.u32 [%0], %1;" ::"r"(addr), "r"(v) : "memory"); }
__device__ __forceinline__ void sts(uint32_t addr, uint2 v) { asm volatile("st.shared.v2.u32 [%0], {%1,%2};" ::"r"(addr), "r"(v.x), "r"(v.y) : "memory"); }
__device__ __forceinline__ void lds(uint32_t& v, uint32_t addr) { asm volatile("ld.shared.u32 %0, [%1];" : "=r"(v) : "r"(addr) : "memory"); }
__device__ __forceinline__ void lds(uint2& v, uint32_t addr) { asm volatile("ld.shared.v2.u32 {%0,%1}, [%2];" : "=r"(v.x), "=r"(v.y) : "r"(addr) : "memory"); }
__host__ __device__ constexpr uint32_t h2(uint32_t h) { return h | (h << 16); }
constexpr uint32_t H_2 = h2(0x4000), H_1_2 = h2(0x3800), H_1_4 = h2(0x3400), H_1_8 = h2(0x3000), H_1_16 = h2(0x2C00), H_1_32 = h2(0x2800),
                   H_N4 = h2(0xC400), H_N2 = h2(0xC000), H_N1_2 = h2(0xB800), H_N1_4 = h2(0xB400), H_N17_4 = h2(0xC440), H_1 = h2(0x3C00), H_N1 = h2(0xBC00);
__device__ __forceinline__ uint32_t hfma(uint32_t a, uint32_t b, uint32_t c) {
  uint32_t r; asm("fma.rn.f16x2 %0, %1, %2, %3;" : "=r"(r) : "r"(a), "r"(b), "r"(c)); return r;
}
__device__ __forceinline__ uint32_t hadd(uint32_t a, uint32_t b) { uint32_t r; asm("add.rn.f16x2 %0, %1, %2;" : "=r"(r) : "r"(a), "r"(b)); return r; }
__device__ __forceinline__ uint32_t hsub(uint32_t a, uint32_t b) { uint32_t r; asm("sub.rn.f16x2 %0, %1, %2;" : "=r"(r) : "r"(a), "r"(b)); return r; }
__device__ __forceinline__ uint2 hfma(uint2 a, uint32_t b, uint2 c) { return make_uint2(hfma(a.x, b, c.x), hfma(a.y, b, c.y)); }
__device__ __forceinline__ uint2 hadd(uint2 a, uint2 b) { return make_uint2(hadd(a.x, b.x), hadd(a.y, b.y)); }
__device__ __forceinline__ uint2 hsub(uint2 a, uint2 b) { return make_uint2(hsub(a.x, b.x), hsub(a.y, b.y)); }
__device__ __forceinline__ uint32_t bmul(uint32_t x, uint32_t k) { uint32_t z; asm("mul.rn.bf16x2 %0, %1, %2;" : "=r"(z) : "r"(x), "r"(k)); return z; }
__device__ __forceinline__ void scale(uint32_t& x, uint32_t k, uint32_t& m) { x = bmul(x, k); m |= x; }
__device__ __forceinline__ void scale(uint2& x, uint32_t k, uint32_t& m) {
  x.x = bmul(x.x, k); x.y = bmul(x.y, k);
  asm("lop3.b32 %0, %0, %1, %2, 0xFE;" : "+r"(m) : "r"(x.x), "r"(x.y));
}
__device__ __forceinline__ void tohalf(uint32_t& z) { z = (z & 0x7FFF7FFFu) * 7 + z; }
__device__ __forceinline__ void tohalf(uint2& z) { tohalf(z.x); tohalf(z.y); }
__device__ __forceinline__ bool out_of_range(uint32_t m) {
  m = __reduce_or_sync(0xffffffffu, m & 0x7FFF7FFFu);
  return (m & 0x78007800u) || (m && !(m & 0x06000600u));
}

template <typename V>
__device__ __forceinline__ void planes8(V (&d)[8], uint32_t dp, uint32_t dq, uint32_t dr, uint32_t ds) {
  const V ec = hfma(d[4], H_N17_4, hadd(d[6], d[2])), oc = hfma(d[3], H_N17_4, hadd(d[5], d[1]));
  sts(dr, hadd(ec, oc)); sts(dr + TWG, hsub(ec, oc));
#pragma unroll
  for (int k = 0; k < 6; k++) d[k] = hsub(d[k + 2], d[k]);
  const V ea = hfma(d[2], H_N4, d[4]), oa = hfma(d[1], H_N4, d[3]);
  sts(dp, hfma(oa, H_1_2, ea)); sts(dq, hfma(oa, H_N1_2, ea));
  sts(ds, hfma(hfma(d[0], H_N4, d[2]), H_N1_4, ea)); sts(ds + TWG, hfma(oa, H_N1_4, hfma(d[3], H_N4, d[5])));
  const V eb = hfma(d[2], H_N1_4, d[4]), ob = hfma(d[1], H_N1_4, d[3]);
  sts(dp + TWG, hfma(ob, H_2, eb)); sts(dq + TWG, hfma(ob, H_N2, eb));
}
template <typename V>
__device__ __forceinline__ void planes4(V (&d)[8], uint32_t dp, uint32_t dq) {
  sts(dp, hadd(d[2], d[1])); sts(dp + TWG, hsub(d[2], d[1]));
  sts(dq, hsub(d[2], d[0])); sts(dq + TWG, hsub(d[3], d[1]));
}

constexpr uint32_t BHI = 256 >> 4, BLO = (128 >> 4) << 16, AHI = 128 >> 4, ALO = (TCOL >> 4) << 16;
__device__ __forceinline__ uint64_t desc(uint32_t lo, uint32_t hi) { uint64_t d; asm("mov.b64 %0, {%1,%2};" : "=l"(d) : "r"(lo), "r"(hi)); return d; }

typedef uint32_t Acc[48];
struct Ctx {
  uint32_t sb;
  uint64_t ad, bd;
  uint32_t b0;
  uint32_t me, ra, tx;
  uint32_t ok;
  bool one;
  uint32_t wg, xs, xr;
  uint32_t w[12];
  uint32_t k, sg;
  const char* o;
  bool on, yes;
};
__device__ __forceinline__ void arrive(uint32_t bar, bool on) {
  asm volatile("{\n.reg .pred p;\nsetp.ne.b32 p, %1, 0;\n@p mbarrier.arrive.shared::cta.b64 _, [%0];\n}" ::"r"(bar), "r"((uint32_t)on) : "memory");
}
template <int S>
__device__ __forceinline__ void release(Ctx& C, uint32_t me, uint32_t tx) {
  asm volatile(
      "{\n.reg .pred p;\n"
      "setp.ne.b32 p, %1, 0;\n"
      "@p mbarrier.arrive.expect_tx.shared::cta.b64 _, [%0], %1;\n}" ::"r"(C.b0 + 16 * S), "r"(tx) : "memory");
  asm volatile(
      "{\n.reg .pred p;\n"
      "setp.eq.b32 p, %0, %2;\n"
      "@p mbarrier.arrive.shared::cluster.b64 _, [%1];\n}" ::"r"(me), "r"(C.ra), "n"(S) : "memory");
}
template <int SYNC, int ID0, int ID1>
__device__ __forceinline__ void bar(uint32_t wg) {
  if (SYNC) asm volatile("{\n.reg .pred p;\nsetp.ne.b32 p, %0, 0;\n@!p bar.sync %1, 256;\n@p bar.sync %2, 256;\n}" ::"r"(wg), "n"(ID0), "n"(ID1) : "memory");
  else asm volatile("{\n.reg .pred p;\nsetp.ne.b32 p, %0, 0;\n@!p bar.arrive %1, 256;\n@p bar.arrive %2, 256;\n}" ::"r"(wg), "n"(ID0), "n"(ID1) : "memory");
}
__device__ __forceinline__ void sent(Ctx& C) { bar<0, 1, 2>(C.wg); }
__device__ __forceinline__ void await_sent(Ctx& C) { bar<1, 2, 1>(C.wg); }
__device__ __forceinline__ void sent2(Ctx& C) { bar<0, 10, 11>(C.wg); }
__device__ __forceinline__ void await_sent2(Ctx& C) { bar<1, 11, 10>(C.wg); }
__device__ __forceinline__ void await_taken(Ctx& C) { bar<1, 3, 4>(C.wg); }
__device__ __forceinline__ void taken(Ctx& C, uint32_t x) { if ((x & blockIdx.y) == 0) bar<0, 4, 3>(C.wg); }

__host__ __device__ constexpr int xoff(int u, int h) { return u * TUNIT + h * 2048; }
template <int B, int OF>
__device__ __forceinline__ void send(const Acc& A, uint32_t addr) {
  asm volatile("st.shared.v4.u32 [%4 + %5], {%0,%1,%2,%3};" ::"r"(A[4 * B]), "r"(A[4 * B + 1]), "r"(A[4 * B + 2]), "r"(A[4 * B + 3]), "r"(addr), "n"(OF) : "memory");
}
template <int B, int OF>
__device__ __forceinline__ void recv(Acc& A, uint32_t addr, bool on) {
  asm volatile("{\n.reg .pred p;\nsetp.ne.b32 p, %6, 0;\n@p ld.shared.v4.u32 {%0,%1,%2,%3}, [%4 + %5];\n}"
               : "+r"(A[4 * B]), "+r"(A[4 * B + 1]), "+r"(A[4 * B + 2]), "+r"(A[4 * B + 3]) : "r"(addr), "n"(OF), "r"((uint32_t)on) : "memory");
}
template <int OF>
__device__ __forceinline__ void fetch4(uint32_t* w, uint32_t addr) {
  asm volatile("ld.shared.v4.u32 {%0,%1,%2,%3}, [%4 + %5];" : "=r"(w[0]), "=r"(w[1]), "=r"(w[2]), "=r"(w[3]) : "r"(addr), "n"(OF) : "memory");
}
template <int I, int N>
__device__ __forceinline__ void add_to(Acc& A, const uint32_t* w, uint32_t sg) {
#pragma unroll
  for (int j = 0; j < N; j++) asm volatile("fma.rn.f16x2 %0, %1, %2, %0;" : "+r"(A[I + j]) : "r"(w[j]), "r"(sg));
}
template <int I, int N>
__device__ __forceinline__ void join(Acc& A, const Acc& B) {
#pragma unroll
  for (int j = I; j < I + N; j++) asm volatile("add.rn.f16x2 %0, %0, %1;" : "+r"(A[j]) : "r"(B[j]));
}
template <int B, int OF>
__device__ __forceinline__ void split(Acc& A, const Acc& Bb, uint32_t* w, uint32_t addr) {
#pragma unroll
  for (int j = 0; j < 4; j++)
    asm volatile("sub.rn.f16x2 %0, %1, %2;\nadd.rn.f16x2 %1, %1, %2;" : "=&r"(w[j]), "+r"(A[4 * B + j]) : "r"(Bb[4 * B + j]));
  asm volatile("st.shared.v4.u32 [%4 + %5], {%0,%1,%2,%3};" ::"r"(w[0]), "r"(w[1]), "r"(w[2]), "r"(w[3]), "r"(addr), "n"(OF) : "memory");
}
__host__ __device__ constexpr int pj(int k) { return 2 * (k >> 2) + (k & 1); }
__host__ __device__ constexpr int pp(int k) { return (k >> 1) & 1; }
template <int K>
__device__ __forceinline__ void rows(const Acc& P, Acc& Q, Acc& R, uint32_t* w) {
#pragma unroll
  for (int i = 0; i < 4; i++) {
    const int j = 8 * pj(K) + 2 * i + pp(K);
    asm volatile(
        "{\n.reg .b32 a, b;\n"
        "fma.rn.f16x2 a, %1, %4, %2;\n fma.rn.f16x2 b, %1, %5, %2;\n fma.rn.f16x2 %1, %1, %6, %2;\n"
        "fma.rn.f16x2 %0, %3, %7, a;\n fma.rn.f16x2 %2, %3, %8, b;\n add.rn.f16x2 %1, %1, %3;\n}"
        : "=r"(w[i]), "+r"(Q[j]), "+r"(R[j]) : "r"(P[j]), "r"(H_1_8), "r"(H_1_2), "r"(H_1_32), "r"(H_1_4), "r"(H_1_16));
  }
}
__device__ __forceinline__ uint32_t tobf(uint32_t h, uint32_t k) {
  uint32_t o;
  asm volatile("{\n.reg .b16 l, u;\n.reg .f32 a, b;\n.reg .b32 t;\nmov.b32 {l, u}, %1;\ncvt.f32.f16 a, l;\ncvt.f32.f16 b, u;\n"
               "cvt.rn.bf16x2.f32 t, b, a;\nmul.rn.bf16x2 %0, t, %2;\n}" : "=r"(o) : "r"(h), "r"(k));
  return o;
}
template <int K>
__device__ __forceinline__ void stg4(const char* o, const uint32_t* r) {
  asm volatile("st.global.cs.v4.u32 [%4 + %5], {%0,%1,%2,%3};" ::"r"(r[0]), "r"(r[1]), "r"(r[2]), "r"(r[3]), "l"(o), "n"(pp(K) * 8 * CH * 2 + pj(K) * 64) : "memory");
}
template <int K, int LAST = 0>
__device__ __forceinline__ void put(const Acc& A, Ctx& C) {
  uint32_t* w = C.w + (LAST ? 4 * (K & 1) : 8);
#pragma unroll
  for (int i = 0; i < 4; i++) w[i] = tobf(A[8 * pj(K) + 2 * i + pp(K)], C.k);
  stg4<K>(C.o, w);
}

constexpr uint64_t OUT_R = 0x252949290ull, OUT_S = 0x084210842108421ull, OUT_M = 0x151551540ull, OUT_F = 0x281015555ull;
constexpr int E0_AT = 6, E1_AT = 27;
__host__ __device__ constexpr int below(uint64_t m, int n) { return __builtin_popcountll(m & ((1ull << n) - 1)); }
static_assert(below(OUT_R, 36) == 12 && below(OUT_S, 60) == 12 && below(OUT_M, 35) == 12 && below(OUT_F, 36) == 12, "pieces");
static_assert(!(OUT_R & 15) && !(OUT_M & 0xC03F) && !(OUT_M & (OUT_M << 1)) && below(OUT_M, 8) <= 1 && below(OUT_M, 12) <= 4 && below(OUT_M, 24) <= 8 && below(OUT_M, 28) <= 9 && !(OUT_F & 0x7E000000) && E0_AT >= 6 && E1_AT >= 27, "order");

__host__ __device__ constexpr int r_out(int n) { return n >= 96 && n < 100 ? n - 96 : n == 124 || n == 125 ? n - 120 : -1; }
__host__ __device__ constexpr int d_out(int n) { return n >= 108 && n < 112 ? n - 108 : n == 122 || n == 123 ? n - 118 : -1; }
__host__ __device__ constexpr int r_in(int n) { return n >= 101 && n < 109 ? n - 101 : n == 130 || n == 131 ? n - 122 : n == 134 || n == 135 ? n - 124 : -1; }
__host__ __device__ constexpr int d_in(int n) { return n >= 112 && n < 120 ? n - 112 : n == 128 || n == 129 ? n - 120 : n == 132 || n == 133 ? n - 122 : -1; }
constexpr uint32_t XU_R = 0x750354, XU_D = 0x425421, XU_F = 0x984210;
template <int N, int FILL>
__device__ __forceinline__ void early(Acc& P, Acc& Q, Acc& R, Acc& S, Ctx& C) {
  if constexpr (FILL) {
    constexpr int I = N - 61;
    if constexpr (I == 0) await_sent(C);
    if constexpr (I >= 0 && I < 6) { fetch4<xoff(unit(XU_F, I), 0)>(C.w, C.xr); fetch4<xoff(unit(XU_F, I), 1)>(C.w + 4, C.xr); }
  } else {
    if constexpr (N == 101 || N == 116) await_sent(C);
    if constexpr (N == 112 || N == 128) await_sent2(C);
    if constexpr (r_in(N) >= 0) {
      constexpr int B = r_in(N);
      fetch4<xoff(unit(XU_R, B / 2), B & 1)>(C.w + 4, C.xr);
    }
    if constexpr (d_in(N) >= 0) recv<d_in(N), xoff(unit(XU_D, d_in(N) / 2), d_in(N) & 1)>(Q, C.xr, C.yes);
  }
}
template <int N, int FILL>
__device__ __forceinline__ void side(Acc& P, Acc& Q, Acc& R, Acc& S, Ctx& C) {
  const uint32_t te = C.sb + BAR_TEMPTY;
  if constexpr (FILL) {
    constexpr int I = N - 36, X = N - 54;
    if constexpr ((OUT_F >> I) & 1) { if (C.on) put<below(OUT_F, I)>(S, C); }
    if constexpr (X >= 0 && X < 6) { send<2 * X, xoff(unit(XU_F, X), 0)>(P, C.xs); send<2 * X + 1, xoff(unit(XU_F, X), 1)>(P, C.xs); }
    if constexpr (X == 5) sent(C);
    if constexpr (N == 66) { if (C.wg) asm volatile("bar.sync 6, 256;" ::: "memory"); }
    if constexpr (N == 71) { if (!C.wg) asm volatile("bar.arrive 6, 256;" ::: "memory"); }
    if constexpr (N >= 61 && N < 67) { if (C.yes) add_to<8 * (N - 61), 8>(P, C.w, C.sg); }
  } else if constexpr (N < 36) {
    if constexpr (N == 0) arrive(te + 16, C.one);
    if constexpr (N < 4) { if (C.on) join<12 * N, 12>(S, Q); }
    if constexpr ((OUT_R >> N) & 1) { if (C.on) put<below(OUT_R, N)>(R, C); }
    if constexpr (N == 30) arrive(te + 24, C.one);
  } else if constexpr (N < 96) {
    if constexpr ((OUT_S >> (N - 36)) & 1) { if (C.on) put<below(OUT_S, N - 36)>(S, C); }
    if constexpr (N == 48) arrive(te + 32, C.one);
    if constexpr (N == 72) arrive(te + 40, C.one);
  } else {
    constexpr int I = N - 108;
    if constexpr (I > 0) {
      if constexpr ((OUT_M >> (I - 1)) & 1) {
        if (C.yes) {
#pragma unroll
          for (int i = 0; i < 4; i++) C.w[8 + i] = tobf(C.w[i], C.k);
        }
        stg4<below(OUT_M, I - 1)>(C.o, C.w + 8);
      }
    }
    if constexpr (I >= 0) {
      if constexpr ((OUT_M >> I) & 1) { if (C.yes) rows<below(OUT_M, I)>(P, Q, R, C.w); }
    }
    if constexpr (N == 110 || N == 122) await_taken(C);
    if constexpr (r_out(N) >= 0) {
      constexpr int X = r_out(N);
      send<2 * X, xoff(unit(XU_R, X), 0)>(R, C.xs); send<2 * X + 1, xoff(unit(XU_R, X), 1)>(R, C.xs);
    }
    if constexpr (r_in(N) >= 0) {
      if (C.yes) {
        add_to<4 * r_in(N), 4>(R, C.w + 4, C.sg);
      }
    }
    if constexpr (d_out(N) >= 0) {
      constexpr int X = d_out(N);
      if (C.yes) { split<2 * X, xoff(unit(XU_D, X), 0)>(P, Q, C.w + 4, C.xs); split<2 * X + 1, xoff(unit(XU_D, X), 1)>(P, Q, C.w, C.xs); }
    }
    if constexpr (N == 99 || N == 111) sent(C);
    if constexpr (N == 109 || N == 125) sent2(C);
    if constexpr (N == 108) taken(C, R[31]);
    if constexpr (N == 120) taken(C, Q[11] | Q[15] | Q[19] | Q[23] | Q[27] | Q[31]);
    if constexpr (I == E0_AT) arrive(te, C.one && ((Q[3] | Q[7]) & blockIdx.y) == 0);
    if constexpr (I == E1_AT) arrive(te + 8, C.one && ((R[47] | Q[35] | Q[39] | Q[43] | Q[47]) & blockIdx.y) == 0);
  }
}
template <int W, int LEAD, int N0, int FILL, int J = 0>
__device__ __forceinline__ void group(Acc& P, Acc& Q, Acc& R, Acc& S, Ctx& C, uint64_t a) {
  constexpr int N = N0 + J;
  if (!C.ok) mbar_wait(C.b0 + 16 * (N % NUST), (N / NUST) & 1);
  wg_fence();
  wgmma192<LEAD && J == 0>(W == 0 ? P : W == 1 ? Q : W == 2 ? R : S, a + (((J / 3) * 2 * TCOL + (J % 3) * 16) >> 4), C.bd + (N % NUST) * (UTILE >> 4), blockIdx.y);
  wg_commit();
  C.ok = mbar_try(C.b0 + 16 * ((N + 1) % NUST), ((N + 1) / NUST) & 1);
  early<N, FILL>(P, Q, R, S, C);
  wg_wait<1>();
  release<(N + NUST - 1) % NUST>(C, N || C.on ? C.me : 0, N || C.on ? C.tx : 0);
  side<N, FILL>(P, Q, R, S, C);
  if constexpr (J < 5) group<W, LEAD, N0, FILL, J + 1>(P, Q, R, S, C, a);
}

__device__ __forceinline__ void fetch(const CUtensorMap* map, uint32_t bytes, uint32_t dst, uint32_t bar, int c, int x, int y, uint64_t pol) {
  asm volatile("{\n.reg .pred p;\nelect.sync _|p, 0xffffffff;\n"
               "@p mbarrier.arrive.expect_tx.shared::cta.b64 _, [%2], %6;\n"
               "@p cp.async.bulk.tensor.3d.shared::cluster.global.mbarrier::complete_tx::bytes.L2::cache_hint [%0], [%1, {%3,%4,%5}], [%2], %7;\n}"
               ::"r"(dst), "l"(map), "r"(bar), "r"(c), "r"(x), "r"(y), "r"(bytes), "l"(pol) : "memory");
}
constexpr uint64_t POL_FIRST = 0x12F0000000000000ull, POL_SAME = 0x10F0000000000000ull;

struct Params { uint8_t* U; uint32_t* ready; int lg, mlg, ufirst, ustep, nunit, umax, nfill, s0, second, nfirst, nall; uint4 un[12]; };

__global__ void __launch_bounds__(NTHREADS, 1) wino_main(const __grid_constant__ CUtensorMap xmap8, const __grid_constant__ CUtensorMap xmap4,
                                                         const __grid_constant__ CUtensorMap xmap1, const __grid_constant__ CUtensorMap xmap0,
                                                         const __nv_bfloat16* __restrict__ xin, const __nv_bfloat16* __restrict__ wgt,
                                                         __nv_bfloat16* __restrict__ out, const Params P) {
  extern __shared__ __align__(1024) uint8_t smem[];
  { const uint32_t l = threadIdx.x * gridDim.x + blockIdx.x; if (l < 9 * CH * CH * 2 / 128) asm volatile("prefetch.global.L2 [%0];" ::"l"((const char*)wgt + l * 128u)); }
  const uint32_t sb = smem_u32(smem);
  const int warp = __shfl_sync(0xffffffffu, threadIdx.x >> 5, 0), lane = threadIdx.x & 31;
  const uint32_t cm = (1u << P.lg) - 1, rank = blockIdx.x & cm, mm = (1u << P.mlg) - 1, mrank = blockIdx.x & mm;
  const int cl = blockIdx.x >> P.lg;
  const int nit = min(P.umax, (P.nunit - cl * P.ufirst + P.ustep - 1) / P.ustep), fu = cl % P.nfill;
  auto first = [&](int i) {
    const int u = cl * P.ufirst + i * P.ustep, q = (u * (205 << (P.lg - 1))) >> 12;
    const int st = P.s0 + (i < nit ? q : fu >> (3 - P.lg));
    const int y = i < nit ? ((u - q * (40 >> P.lg)) * 6 << P.lg) + 6 * rank : 240 + ((fu & ((8 >> P.lg) - 1)) * 2 << P.lg) + 2 * rank;
    return (st & 7) * 64 + ((st >> 3) * 256 + y) * IMG;
  };

  auto origin = [&](int i) { int o; asm volatile("ld.shared.u32 %0, [%1];" : "=r"(o) : "r"(sb + SM_ORG + 4 * i)); return o; };
  if (warp == 11 && lane < 7) sts(sb + SM_ORG + 4 * lane, (uint32_t)first(min(lane, nit)));

  if (warp != 11) asm volatile("barrier.cluster.arrive.relaxed.aligned;" ::: "memory");
  if (warp == 10) {
    sts(sb + SM_EXP, min(sample_exp((const char*)wgt + lane * (4 * 5168), 5168), 240u));
    asm volatile("bar.arrive 11, 288;" ::: "memory");
  }
  if (warp == 9) {
    const uint32_t e = sample_exp((const char*)xin + ((uint32_t)(first(0) + 2 * lane + (lane & 1) * IMG) * (CH * 2u) + lane % 6 * 64), CH / 2 + 16);
    sts(sb + SM_EXP + 4, e ? min(e, 138u) : 120);
    asm volatile("bar.arrive 12, 192;\nbar.arrive 13, 288;" ::: "memory");
  }
  if (warp < 8) {
    const int t0 = warp * gridDim.x + blockIdx.x;
    if (P.second || t0 >= NFILT) { cluster_wait(); asm volatile("bar.sync 11, 288;" ::: "memory"); }
    if (!P.second) {
      bool ok = true;
      if (t0 >= NFILT) made(P.ready, 1);
#pragma unroll 1
      for (int t = t0; t < NFILT; t += 8 * gridDim.x) ok = filter_task(wgt, P.U, t, lane, sb + SM_EXP, t == t0, t + 8 * gridDim.x >= NFILT, P.ready) && ok;
      if (!ok) atomicOr(P.ready, 1u << 31);
      made(P.ready, 1024);
    }
  }
  if (warp == 8) {
    uint32_t v; asm volatile("ld.volatile.global.u32 %0, [%1];" : "=r"(v) : "l"(P.ready) : "memory");
    if (v < P.nfirst) __nanosleep(100);
  }
  if (threadIdx.x == 352) {
    for (int i = 0; i < 2 * NUST; i++) { mbar_init(sb + BAR_U + 16 * i, 1); mbar_init(sb + BAR_U + 16 * i + 8, mm + 1); }
    for (int i = 0; i < 6; i++) { mbar_init(sb + BAR_TFULL + 8 * i, 5); mbar_init(sb + BAR_TEMPTY + 8 * i, 8); }
    sts(sb + SM_FLAG, 0u);
    asm volatile("fence.mbarrier_init.release.cluster;" ::: "memory");
    for (int i = 0; i < 2 * NUST; i++) mbar_expect_tx(sb + BAR_U + 16 * i, UTILE);
  }
  const uint32_t rbar = __shfl_sync(0xffffffffu, sb + BAR_RFULL + (warp & 3) * 16, 0), rbuf = sb + SM_R + (warp & 3) * (2 * RSLOT);
  if (warp >= 12) {
    if (lane == 0) {
      mbar_init(rbar, 1); mbar_init(rbar + 8, 1);
      asm volatile("fence.mbarrier_init.release.cluster;" ::: "memory");
    }
    __syncwarp();
    if (!P.second) __nanosleep(300);
    const int o = first(0);
#pragma unroll
    for (int i = 0; i < 2; i++)
      fetch(nit ? &xmap0 : &xmap4, nit ? RSLOT : RSLOT / 2, rbuf + i * RSLOT, rbar + 8 * i, 0, (o & 511) - 1 + (warp & 3) * 16 + i * 4, (o >> 9) - 1, POL_SAME);
  }
  __syncwarp();
  if (warp == 11) asm volatile("barrier.cluster.arrive.relaxed.aligned;" ::: "memory");
  if (warp == 8 || warp > 10) cluster_wait();
  if (warp > 10) asm volatile("bar.sync 12, 192;" ::: "memory");
  if (warp < 8) asm volatile("bar.sync 13, 288;" ::: "memory");
  uint2 ex;
  lds(ex, sb + SM_EXP);
  const uint32_t kin = h2((139 - ex.y) << 7);

  if (warp >= 12) {
    asm volatile("setmaxnreg.dec.sync.aligned.u32 40;");
    const int wi = warp - 12;
    const uint32_t tb = __shfl_sync(0xffffffffu, sb + SM_T + ((lane >> 1) & 3) * TCOL + (wi * 16 + (lane >> 3)) * 16 + (lane & 1) * 8, lane);
    const uint32_t src = rbuf + __shfl_sync(0xffffffffu, lane * 8, lane);
    const uint32_t nb = __shfl_sync(0xffffffffu, lane & blockIdx.y, lane);
    int o = origin(0), x = (o & 511) - 1 + wi * 16, y = (o >> 9) - 1;
    uint32_t m = 0;
    auto chunk = [&](auto fill, int i, uint32_t c, int xn, int yn) {
      constexpr int NR = fill.value ? 4 : 8;
      const CUtensorMap* const map = fill.value ? &xmap4 : &xmap8;
      const uint4 un = P.un[6 * fill.value + c];
      const bool turn = c == 5, half = fill.value || (turn && i + 1 == nit);
      const CUtensorMap* const map1 = half ? &xmap4 : &xmap8;
      const int c1 = turn ? 0 : c * 32 + 32, x1 = turn ? xn : x, y1 = turn ? yn : y;
      const uint32_t n1 = half ? RSLOT / 2 : RSLOT;
#pragma unroll
      for (int q = 0; q < 4; q++) {
        const uint32_t sl = (q & 1) * RSLOT, rb = rbar + (q & 1) * 8;
        uint2 d[8];
        mbar_wait_sleep(rb, q >> 1);
#pragma unroll
        for (int r = 0; r < NR; r++) lds(d[r], src + sl + r * RROW);
#pragma unroll
        for (int r = 0; r < NR; r++) scale(d[r], kin, m);
        if (q < 2) fetch(!fill.value && i + c == 0 ? &xmap0 : map, NR * RROW | (m & nb), rbuf + sl, rb, c * 32, x + 8 + 4 * q, y, c & 1 ? POL_FIRST : POL_SAME);
        else if (!fill.value || !turn) fetch(map1, n1 | (m & nb), rbuf + sl, rb, c1, x1 + 4 * q - 8, y1, c & 1 ? POL_SAME : POL_FIRST);
#pragma unroll
        for (int r = 0; r < NR; r++) tohalf(d[r]);
        if (q == 0 && (!fill.value || c < 3)) mbar_wait_sleep(sb + BAR_TEMPTY + 8 * c, (i & 1) ^ (c < 2));
        if (q == 0 && wi == 0) TRACE(2, tn);
        const uint32_t t = tb + 64 * q;
        if (fill.value) planes4(d, t + un.x, t + un.y);
        else planes8(d, t + un.x, t + un.y, t + un.z, t + un.w);
      }
      if (turn) {
        if (out_of_range(m)) asm volatile("red.shared.or.b32 [%0], %1;" ::"r"(sb + SM_FLAG), "r"(1u << i) : "memory");
        m = 0; x = xn; y = yn;
      }
      asm volatile("fence.proxy.async.shared::cta;" ::: "memory");
      __syncwarp();
      arrive_elect(sb + BAR_TFULL + 8 * c);
    };
#pragma unroll 1
    for (int i = 0; i < nit; i++) {
      o = origin(i + 1);
#pragma unroll 1
      for (uint32_t c = 0; c < 6; c++) chunk(std::false_type(), i, c, (o & 511) - 1 + wi * 16, (o >> 9) - 1);
    }
#pragma unroll 1
    for (uint32_t c = 0; c < 6; c++) chunk(std::true_type(), nit, c, 0, 0);
    cluster_sync();
  } else if (warp >= 8) {
    asm volatile("setmaxnreg.dec.sync.aligned.u32 24;");
    if (warp < 10) {
      const uint32_t g = warp - 8, s0 = mrank ^ (13 * g & mm);
      const uint32_t ring = sb + SM_U + g * (NUST * UTILE), ub = sb + BAR_U + g * (NUST * 16);
      if (warp == 8) {
        uint32_t v, i = 0;
        do { asm volatile("ld.acquire.gpu.global.u32 %0, [%1];" : "=r"(v) : "l"(P.ready) : "memory"); if (++i > 5000000u) __trap(); } while ((v & 1023) < P.nfirst);
        asm volatile("bar.arrive 7, 64;" ::: "memory");
      }
      asm volatile("bar.sync 9, 64;" ::: "memory");
      asm volatile("fence.proxy.async.global;" ::: "memory");
      uint32_t ph = 1;
#pragma unroll 1
      for (int i = 0; i <= nit; i++) {
        const uint8_t* from = P.U + g * UWG + (i < nit ? 0 : NROUND * NUST * UTILE);
#pragma unroll 1
        for (uint32_t t = 0; t < (i < nit ? NROUND : NFROUND); t++, ph ^= 1, from += NUST * UTILE) {
          if (i == 0 && t == 36 / NUST) asm volatile("bar.sync 8, 96;\nfence.proxy.async.global;" ::: "memory");
#pragma unroll 1
          for (uint32_t s = s0; mm == 15 ? s < 9 : s < 8 || (s < 16 && s0 == (4 & mm)); s = s + mm + 1 < 8 ? s + mm + 1 : s < 8 && mm < 15 ? 8 : 16) {
            mbar_wait(ub + 16 * s + 8, ph);
            asm volatile(
                "{\n.reg .pred p;\n"
                "elect.sync _|p, 0xffffffff;\n"
                "@p cp.async.bulk.shared::cluster.global.mbarrier::complete_tx::bytes.multicast::cluster [%0], [%1], %2, [%4], %3;\n}"
                ::"r"(ring + s * UTILE), "l"(from + s * UTILE), "n"(UTILE), "h"((uint16_t)((2u << mm) - 1)), "r"(ub + 16 * s) : "memory");
          }
        }
      }
    } else if (warp == 10) {
      uint32_t v, i = 0;
      do { asm volatile("ld.acquire.gpu.global.u32 %0, [%1];" : "=r"(v) : "l"(P.ready) : "memory"); if (++i > 5000000u) __trap(); } while (((v >> 10) & 1023) < P.nfirst);
      if (v >> 31) asm volatile("red.shared.or.b32 [%0], %1;" ::"r"(sb + SM_FLAG), "r"(0xFFFFu) : "memory");
      __syncwarp();
      asm volatile("bar.arrive 8, 96;" ::: "memory");
      asm volatile("bar.sync 7, 64;" ::: "memory");
      if (lane == 0 && atomicAdd(P.ready + 32, 1) == P.nall - 1) P.ready[0] = P.ready[32] = 0;
      __syncwarp();
      asm volatile("griddepcontrol.launch_dependents;");
      auto ahead = [&](int i, uint32_t sl, int r) {
        const int o = origin(i), nr = i < nit ? 6 : 2;
        auto row = [&](int y) {
          asm volatile("{\n.reg .pred p;\nelect.sync _|p, 0xffffffff;\n@p cp.async.bulk.prefetch.tensor.3d.L2.global [%0, {%1,%2,%3}];\n}"
                       ::"l"(&xmap1), "r"(sl * 64), "r"((o & 511) - 1), "r"((o >> 9) + y) : "memory");
        };
        if (r < nr) row(r);
        if (r == 0 && rank == 0) row(-1);
        if (r + 1 == nr && rank == cm) row(nr);
      };
      uint32_t ph = 0;
#pragma unroll 1
      for (int i = 0; i <= nit; i++) {
#pragma unroll 1
        for (uint32_t t = 0; t < (i < nit ? NROUND : NFROUND - 3); t++, ph ^= 1) {
#pragma unroll 1
          for (int n = P.second ? 400 : 20; n && !mbar_try(sb + BAR_U + 16 * rank, ph); n--) __nanosleep(100);
          if (t - 1 < 6) ahead(i, 2, t - 1);
          if (i < nit && t - 6 < 6) ahead(i + 1, 0, t - 6);
          if (i < nit && t - 10 < 6) ahead(i + 1, 1, t - 10);
          if (((cl + t) & 7) == 0 && !P.second) {
            const uint32_t r = i == nit ? NROUND + t + 3 : t + 3 < NROUND || i + 1 == nit ? t + 3 : t + 3 - NROUND;
            if (lane < (rank == 4 ? 4 : 2))
              asm volatile("cp.async.bulk.prefetch.L2.global [%0], %1;" ::"l"(P.U + ((lane & 1) * UWG + (r * NUST + (lane >> 1 ? 8 : rank)) * UTILE)), "n"(UTILE) : "memory");
            __syncwarp();
          }
        }
      }
    } else {
      const uint32_t tb = sb + SM_T + ((lane >> 2) & 3) * TCOL + (64 + (lane >> 4)) * 16 + (lane & 3) * 4;
      uint32_t iph = 0;
#pragma unroll 1
      for (int i = 0; i <= nit; i++, iph ^= 1) {
        const int o = origin(i), x = (o & 511) + 63 + (lane >> 4), y = (o >> 9) - 1, nr = i < nit ? 8 : 4;
        const char* p = (const char*)xin + (uint32_t)(o + 63 + (lane >> 4)) * (CH * 2u) + (lane & 15) * 4;
        uint32_t m = 0;
#pragma unroll 1
        for (uint32_t c = 0; c < 6; c++, p += 64) {
          uint32_t d[8];
#pragma unroll
          for (int r = 0; r < 8; r++) {
            d[r] = 0;
            if (x < IMG && (uint32_t)(y + r) < IMG && r < nr) asm volatile("ld.global.nc.u32 %0, [%1];" : "=r"(d[r]) : "l"(p + (r - 1) * ROWB));
          }
#pragma unroll
          for (int r = 0; r < 8; r++) { scale(d[r], kin, m); tohalf(d[r]); }
          if (i < nit || c < 3) mbar_wait_sleep(sb + BAR_TEMPTY + 8 * c, iph ^ (c < 2));
          if (i < nit) planes8(d, tb + unit(UN_P, c) * TUNIT, tb + unit(UN_Q, c) * TUNIT, tb + unit(UN_R, c) * TUNIT, tb + unit(UN_S, c) * TUNIT);
          else planes4(d, tb + unit(UN_FP, c) * TUNIT, tb + unit(UN_FQ, c) * TUNIT);
          if (c == 5 && (m & 0x78007800u)) asm volatile("red.shared.or.b32 [%0], %1;" ::"r"(sb + SM_FLAG), "r"(1u << i) : "memory");
          asm volatile("fence.proxy.async.shared::cta;" ::: "memory");
          __syncwarp();
          arrive_elect(sb + BAR_TFULL + 8 * c);
        }
      }
      if (P.second == 2) asm volatile("griddepcontrol.wait;" ::: "memory");
    }
    __syncwarp();
    cluster_sync();
  } else {
    const uint32_t ek = ex.x ? ex.x + ex.y - 119 : 0;
    asm volatile("setmaxnreg.inc.sync.aligned.u32 224;");
    const int wg = warp >> 2;
    Ctx C;
    C.sb = sb; C.wg = wg;
    C.b0 = sb + BAR_U + wg * (NUST * 16);
    C.bd = desc(BLO + (((sb + SM_U + wg * (NUST * UTILE)) & 0x3FFFF) >> 4), BHI);
    C.ad = desc(ALO + (((sb + SM_T + wg * TWG) & 0x3FFFF) >> 4), AHI);
    C.me = __shfl_sync(0xffffffffu, threadIdx.x & 127, lane); C.tx = __shfl_sync(0xffffffffu, (threadIdx.x & 127) == 0 ? UTILE : 0, lane);
    asm volatile("mapa.shared::cluster.u32 %0, %1, %2;" : "=r"(C.ra) : "r"(C.b0 + 16 * lane + 8), "r"(((lane == 8 && mm < 15 ? 4 : lane) ^ 13 * wg) & mm));
    C.ok = 0;
    const uint32_t t16 = __shfl_sync(0xffffffffu, (warp & 3) * 512 + lane * 16, lane);
    C.one = (t16 & 511) == 0;
    C.xs = sb + SM_T + wg * TWG + t16;
    C.xr = sb + SM_T + (wg ^ 1) * TWG + t16;
    C.k = h2(ek << 7); C.sg = wg ? H_1 : H_N1;
    C.yes = C.sb != gridDim.x;
    const int drow = wg ? -2 * ROWB : 2 * ROWB;
    const char* const ob = (const char*)out + (uint32_t)(((warp & 3) * 16 + (lane >> 2)) * CH + (lane & 3) * 8) * 2u;
    C.o = ob;
#pragma unroll
    for (int i = 0; i < 12; i++) C.w[i] = 0;

    Acc A0, A1, A2, A3;
#pragma unroll
    for (int j = 0; j < 48; j++) { A0[j] = 0; A1[j] = 0; A2[j] = 0; A3[j] = 0; }
#define G(W, LEAD, N0, FILL, U) group<W, LEAD, N0, FILL>(A0, A1, A2, A3, C, C.ad + (U) * (TUNIT >> 4))
    uint32_t ph = 0;
#pragma unroll 1
    for (int item = 0;; item++) {
      C.on = item != 0;
      if (P.second && item == 2) {
        const int wait = (5 - nit) * 28000 - PAUSE_B;
        uint32_t c0, c;
        asm volatile("mov.u32 %0, %%clock;" : "=r"(c0));
        do { __nanosleep(500); asm volatile("mov.u32 %0, %%clock;" : "=r"(c)); } while ((int)(c - c0) < wait);
      }
      C.ad += item & blockIdx.y; C.bd += item & blockIdx.y;
      mbar_wait(sb + BAR_TFULL, ph);
      G(0, 1, 0, 0, unit(UN_P, 0));
      G(1, 1, 6, 0, unit(UN_Q, 0));
      mbar_wait(sb + BAR_TFULL + 8, ph);
      G(0, 0, 12, 0, unit(UN_P, 1)); G(1, 0, 18, 0, unit(UN_Q, 1));
      mbar_wait(sb + BAR_TFULL + 16, ph);
      G(0, 0, 24, 0, unit(UN_P, 2)); G(1, 0, 30, 0, unit(UN_Q, 2));
      C.o -= 2 * drow;
      if (item == nit) break;
      G(2, 1, 36, 0, unit(UN_R, 0)); G(2, 0, 42, 0, unit(UN_R, 1)); G(2, 0, 48, 0, unit(UN_R, 2));
      mbar_wait(sb + BAR_TFULL + 24, ph);
      G(2, 0, 54, 0, unit(UN_R, 3)); G(0, 0, 60, 0, unit(UN_P, 3)); G(1, 0, 66, 0, unit(UN_Q, 3));
      mbar_wait(sb + BAR_TFULL + 32, ph);
      G(2, 0, 72, 0, unit(UN_R, 4)); G(0, 0, 78, 0, unit(UN_P, 4)); G(1, 0, 84, 0, unit(UN_Q, 4));
      mbar_wait(sb + BAR_TFULL + 40, ph);
      G(2, 0, 90, 0, unit(UN_R, 5)); G(0, 0, 96, 0, unit(UN_P, 5)); G(1, 0, 102, 0, unit(UN_Q, 5));
      ph ^= 1;
      C.o = ob + (uint32_t)(origin(item) + (2 + wg) * IMG) * (CH * 2u);
      G(3, 1, 108, 0, unit(UN_S, 0)); G(3, 0, 114, 0, unit(UN_S, 1)); G(3, 0, 120, 0, unit(UN_S, 2));
      G(3, 0, 126, 0, unit(UN_S, 3)); G(3, 0, 132, 0, unit(UN_S, 4)); G(3, 0, 138, 0, unit(UN_S, 5));
      C.o += drow;
    }
    mbar_wait(sb + BAR_TFULL + 24, ph);
    G(0, 0, 36, 1, unit(UN_FP, 3));
    mbar_wait(sb + BAR_TFULL + 32, ph);
    G(0, 0, 42, 1, unit(UN_FP, 4));
    mbar_wait(sb + BAR_TFULL + 40, ph);
    G(0, 0, 48, 1, unit(UN_FP, 5));
    G(1, 0, 54, 1, unit(UN_FQ, 3)); G(1, 0, 60, 1, unit(UN_FQ, 4)); G(1, 0, 66, 1, unit(UN_FQ, 5));
#undef G
    wg_wait<0>();
    asm volatile("barrier.cluster.arrive.relaxed.aligned;" ::: "memory");
    uint32_t redo;
    asm volatile("ld.shared.u32 %0, [%1];" : "=r"(redo) : "r"(sb + SM_FLAG) : "memory");
    if (cl < P.nfill) {
      C.o = ob + (uint32_t)(origin(nit) + wg * IMG) * (CH * 2u);
      join<0, 48>(A1, A0);
      put<0, 1>(A1, C); put<1, 1>(A1, C); put<2, 1>(A1, C); put<3, 1>(A1, C); put<4, 1>(A1, C); put<5, 1>(A1, C);
      put<6, 1>(A1, C); put<7, 1>(A1, C); put<8, 1>(A1, C); put<9, 1>(A1, C); put<10, 1>(A1, C); put<11, 1>(A1, C);
    }
    if (ek - 1 > 253) redo = 0xFFFF;
    if (redo) {
      asm volatile("bar.sync 5, 256;" ::: "memory");
      const int k = threadIdx.x;
#pragma unroll 1
      for (int i = 0; i < nit + (cl < P.nfill); i++) {
        if (!((redo >> i) & 1) || k >= CH) continue;
        const int o = origin(i);
#pragma unroll 1
        for (int t = 0; t < (i < nit ? 48 : 16); t++) {
          const int y = (o >> 9) + (t >> 3), x = (o & 511) + (t & 7) * 8;
          float acc[8];
#pragma unroll
          for (int j = 0; j < 8; j++) acc[j] = 0.f;
#pragma unroll 1
          for (int rs = 0; rs < 9; rs++) {
            const int yy = y + rs / 3 - 1, xx = x + rs % 3 - 1;
            if ((uint32_t)yy >= IMG) continue;
#pragma unroll 1
            for (int c = 0; c < CH; c += 2) {
              const float w0 = __bfloat162float(wgt[(rs * CH + c) * CH + k]), w1 = __bfloat162float(wgt[(rs * CH + c + 1) * CH + k]);
#pragma unroll
              for (int j = 0; j < 8; j++) {
                if ((uint32_t)(xx + j) < IMG) {
                  const uint32_t v = __ldg(reinterpret_cast<const uint32_t*>(xin + (yy * IMG + xx + j) * CH + c));
                  acc[j] = fmaf(__uint_as_float(v & 0xFFFF0000u), w1, fmaf(__uint_as_float(v << 16), w0, acc[j]));
                }
              }
            }
          }
#pragma unroll
          for (int j = 0; j < 8; j++) out[(y * IMG + x + j) * CH + k] = __float2bfloat16(acc[j]);
        }
      }
    }
    __syncwarp();
    asm volatile("barrier.cluster.wait.aligned;" ::: "memory");
  }
}

typedef CUresult (*EncFn)(CUtensorMap*, CUtensorMapDataType, cuuint32_t, void*, const cuuint64_t*, const cuuint64_t*,
                          const cuuint32_t*, const cuuint32_t*, CUtensorMapInterleave, CUtensorMapSwizzle,
                          CUtensorMapL2promotion, CUtensorMapFloatOOBfill);

}

extern "C" void kernel_launch(void* const* d_in, const int* in_sizes, int n_in, void* d_out, int out_size) {
  const __nv_bfloat16* x = (const __nv_bfloat16*)d_in[0];
  const __nv_bfloat16* w = (const __nv_bfloat16*)d_in[1];
  __nv_bfloat16* out = (__nv_bfloat16*)d_out;

  static EncFn enc = nullptr;
  static void *U = nullptr, *ready = nullptr;
  if (!enc) {
    cudaGetSymbolAddress(&U, g_U);
    cudaGetSymbolAddress(&ready, g_ready);
    void* fn = nullptr; cudaDriverEntryPointQueryResult st;
    cudaGetDriverEntryPoint("cuTensorMapEncodeTiled", &fn, cudaEnableDefault, &st);
    enc = (EncFn)fn;
    cudaFuncSetAttribute(wino_main, cudaFuncAttributeMaxDynamicSharedMemorySize, SMEM_BYTES);
    cudaFuncSetAttribute(wino_main, cudaFuncAttributeNonPortableClusterSizeAllowed, 1);
  }
  CUtensorMap xmap[4];
  for (int i = 0; i < 4; i++) {
    cuuint64_t dims[3] = {CH, IMG, IMG};
    cuuint64_t str[2] = {CH * 2, (cuuint64_t)ROWB};
    cuuint32_t box[3] = {i != 2 ? 32u : 64u, i != 2 ? 4u : 66u, i == 2 ? 1u : i == 1 ? 4u : 8u};
    cuuint32_t es[3] = {1, 1, 1};
    enc(&xmap[i], CU_TENSOR_MAP_DATA_TYPE_BFLOAT16, 3, (void*)x, dims, str, box, es, CU_TENSOR_MAP_INTERLEAVE_NONE,
        CU_TENSOR_MAP_SWIZZLE_NONE, i == 3 ? CU_TENSOR_MAP_L2_PROMOTION_NONE : CU_TENSOR_MAP_L2_PROMOTION_L2_128B, CU_TENSOR_MAP_FLOAT_OOB_FILL_NONE);
  }
  cudaLaunchConfig_t cfg = {};
  cudaLaunchAttribute attr[2];
  cfg.blockDim = dim3(NTHREADS);
  cfg.dynamicSmemBytes = SMEM_BYTES;
  cfg.stream = cudaStreamPerThread;
  attr[0].id = cudaLaunchAttributeClusterDimension;
  attr[0].val.clusterDim.x = 16; attr[0].val.clusterDim.y = 1; attr[0].val.clusterDim.z = 1;
  attr[1].id = cudaLaunchAttributeProgrammaticStreamSerialization;
  attr[1].val.programmaticStreamSerializationAllowed = 1;
  cfg.attrs = attr;
  static int mlg = 0, ns = 0, n2 = 0;
  if (!mlg) {
    cfg.numAttrs = 1;
    cfg.gridDim = dim3(128);
    int n[3] = {0, 0, 0};
    for (int i = 0; i < 3; i++) {
      attr[0].val.clusterDim.x = i == 2 ? 2 : 16 >> i;
      if (cudaOccupancyMaxActiveClusters(&n[i], wino_main, &cfg) != cudaSuccess) { n[i] = 0; cudaGetLastError(); }
    }
    mlg = n[0] >= 7 ? 4 : 3;
    ns = mlg == 4 ? 2 * n[0] : n[1];
    ns = ns < 1 ? 1 : ns > 16 ? 16 : ns;
    n2 = n[2] - 4 * ns;
  }
  const int nf = 4 * (16 - ns), nb = n2 < nf ? nf : n2 > 5 * nf ? 5 * nf : n2;
  Params P = {(uint8_t*)U, (uint32_t*)ready, 3, mlg, 5, 1, 5 * ns, 5, ns, 0, 0, 8 * ns, 8 * ns + 2 * nb};
  for (int c = 0; c < 6; c++) {
    P.un[c] = make_uint4(unit(UN_P, c) * TUNIT, unit(UN_Q, c) * TUNIT, unit(UN_R, c) * TUNIT, unit(UN_S, c) * TUNIT);
    P.un[6 + c] = make_uint4(unit(UN_FP, c) * TUNIT, unit(UN_FQ, c) * TUNIT, 0, 0);
  }
  attr[0].val.clusterDim.x = 1 << mlg;
  cfg.numAttrs = 1;
  cfg.gridDim = dim3(8 * ns);
  cudaLaunchKernelEx(&cfg, wino_main, xmap[0], xmap[1], xmap[2], xmap[3], x, w, out, P);
  if (!nb) return;
  cudaStreamCaptureStatus cap = cudaStreamCaptureStatusNone;
  cudaStreamIsCapturing(cfg.stream, &cap);
  P.lg = P.mlg = 1; P.ufirst = 1; P.ustep = nb; P.nunit = 5 * nf; P.nfill = nf; P.s0 = ns; P.second = cap == cudaStreamCaptureStatusActive ? 1 : 2;
  attr[0].val.clusterDim.x = 2;
  cfg.numAttrs = 2;
  cfg.gridDim = dim3(2 * nb);
  cudaLaunchKernelEx(&cfg, wino_main, xmap[0], xmap[1], xmap[2], xmap[3], x, w, out, P);
}
```

```cpp
#include <cuda_runtime.h>
#include <cuda.h>
#include <cuda_bf16.h>
#include <stdint.h>
#include <type_traits>

namespace {

constexpr int IMG = 512;
constexpr int CH = 192;
constexpr int ROWB = IMG * CH * 2;
constexpr int TCOL = 66 * 16;
constexpr int TUNIT = 4 * TCOL;
constexpr int TWG = 12 * TUNIT;
constexpr int RROW = 4 * 64;
constexpr int RSLOT = 8 * RROW;
constexpr int UTILE = 192 * 32;
constexpr int NUST = 9;
constexpr int NROUND = 144 / NUST, NFROUND = 72 / NUST;
constexpr int UWG = (NROUND + NFROUND) * NUST * UTILE;
constexpr int SM_U = 0;
constexpr int SM_R = SM_U + 2 * NUST * UTILE;
constexpr int SM_T = 131072 - 1024;
constexpr int SM_BAR = SM_T + 2 * TWG;
static_assert(SM_R + 4 * 2 * RSLOT <= SM_T, "smem");
constexpr int SMEM_BYTES = SM_BAR + 256 + 32 * NUST + 16;
constexpr int NTHREADS = 512;
constexpr uint32_t BAR_TFULL = SM_BAR, BAR_TEMPTY = SM_BAR + 48, SM_FLAG = SM_BAR + 96, SM_ORG = SM_BAR + 100, SM_EXP = SM_BAR + 256 + 32 * NUST, BAR_RFULL = SM_BAR + 128,
                   BAR_U = SM_BAR + 256;
static_assert(SMEM_BYTES <= 232448 && SM_R % 128 == 0, "smem");

__host__ __device__ constexpr int group_of(int q, int c) {
  return q == 0 ? (c < 3 ? 2 * c : 3 * c + 1) : q == 1 ? (c < 3 ? 2 * c + 1 : 3 * c + 2) : q == 2 ? (c < 3 ? 6 + c : 3 * c) : q == 3 ? 18 + c
       : q == 4 ? 24 + (c < 3 ? 2 * c : 3 + c) : 24 + (c < 3 ? 2 * c + 1 : 6 + c);
}
constexpr uint32_t UN_P = 0x141820, UN_Q = 0x252941, UN_R = 0x030A53, UN_S = 0xA98B76, UN_FP = 0xA53820, UN_FQ = 0xB76941;
__host__ __device__ constexpr uint32_t unit(uint32_t tab, int c) { return (tab >> (4 * c)) & 15; }

__device__ __align__(1024) uint8_t g_U[2 * UWG];
__device__ uint32_t g_ready[64];
#define TRACE(row, i)

__device__ __forceinline__ void cluster_wait() { asm volatile("barrier.cluster.wait.acquire.aligned;" ::: "memory"); }
__device__ __forceinline__ uint32_t sample_exp(const char* p, uint32_t stride) {
  uint32_t m = 0;
  uint4 v[4];
#pragma unroll
  for (int i = 0; i < 4; i++)
    asm volatile("ld.global.nc.v4.u32 {%0,%1,%2,%3}, [%4];" : "=r"(v[i].x), "=r"(v[i].y), "=r"(v[i].z), "=r"(v[i].w) : "l"(p + i * stride));
  cluster_wait();
#pragma unroll
  for (int i = 0; i < 4; i++)
    m = __vmaxu2(__vmaxu2(m, __vmaxu2(v[i].x & 0x7FFF7FFFu, v[i].y & 0x7FFF7FFFu)), __vmaxu2(v[i].z & 0x7FFF7FFFu, v[i].w & 0x7FFF7FFFu));
  return __reduce_max_sync(0xffffffffu, max(m & 0xFFFFu, m >> 16)) >> 7;
}

constexpr int PQBITS = 9;
constexpr int NFILT = 2 * 6 * 24 * 3;
__device__ __forceinline__ void made(uint32_t* ready, uint32_t n) {
  asm volatile("fence.proxy.async.global;\nbar.sync 10, 256;" ::: "memory");
  if (threadIdx.x == 0) asm volatile("red.release.gpu.global.add.u32 [%0], %1;" ::"l"(ready), "r"(n) : "memory");
  __syncwarp();
}
__device__ __forceinline__ bool filter_task(const __nv_bfloat16* __restrict__ w, uint8_t* U, int t, int lane, uint32_t ew, bool first, bool last, uint32_t* ready) {
  const int wg = t & 1, blk = (t >> 1) % 6, co = (t / 12) % 24, s = t / (12 * 24);
  const int k = blk * 32 + ((lane >> 1) & 3) * 8 + (lane >> 3) * 2 + (lane & 1);
  const unsigned short* wp = reinterpret_cast<const unsigned short*>(w) + ((wg * 6 + s) * CH + co * 8) * CH + k;
  const int dr = wg ? -3 * CH * CH : 3 * CH * CH;
  uint32_t g[3][8];
#pragma unroll
  for (int r = 0; r < 3; r++)
#pragma unroll
    for (int i = 0; i < 8; i++) asm volatile("ld.global.nc.u16 %0, [%1];" : "=r"(g[r][i]) : "l"(wp + r * dr + i * CH));
  const int chunk = co >> 2;
  uint8_t* const u = U + wg * UWG + (3 * ((co >> 1) & 1) + s) * UTILE + (blk * 4 + (lane >> 3)) * 256 + (co & 1) * 128 + (lane & 7) * 16;
  if (first) { cluster_wait(); asm volatile("bar.sync 11, 288;" ::: "memory"); }
  asm volatile("ld.shared.u32 %0, [%0];" : "+r"(ew)::"memory");
  const float su = __uint_as_float((249 - ew) << 23), low = __uint_as_float(15u << 23);
  const float na = wg ? 128.f / 90.f : 1.f / 1.40625f, sg = wg ? -1.f : 1.f;
  float v[5][8], m = 0.f;
#pragma unroll
  for (int i = 0; i < 8; i++) {
    const float a = __uint_as_float(g[0][i] << 16) * su, b = __uint_as_float(g[1][i] << 16) * su, c = __uint_as_float(g[2][i] << 16) * su;
    asm("{\n.reg .f32 t;\nmax.NaN.f32 t, %1, %2;\nmax.NaN.f32 %0, %0, %3;\nmax.NaN.f32 %0, %0, t;\n}" : "+f"(m) : "f"(fabsf(a)), "f"(fabsf(b)), "f"(fabsf(c)));
    const float e = fmaf(0.25f, c, a) * na, o = b * (0.5f * na), d = fmaf(a + c, sg, b);
    v[0][i] = e + o; v[1][i] = (e - o) * sg; v[2][i] = d * (low / -4.5f); v[3][i] = a * (-sg * low); v[4][i] = d * (0.5f * low);
  }
#pragma unroll
  for (int q = 0; q < 5; q++) {
    uint32_t pk[4];
#pragma unroll
    for (int i = 0; i < 4; i++) {
      if (q < 2) {
        asm("cvt.rz.f16x2.f32 %0, %1, %2;" : "=r"(pk[i]) : "f"(v[q][2 * i + 1]), "f"(v[q][2 * i]));
        pk[i] = (pk[i] + (0x00010001u << (10 - PQBITS))) & ~((0x00010001u << (11 - PQBITS)) - 0x00010001u);
      } else {
        asm("cvt.rn.bf16x2.f32 %0, %1, %2;" : "=r"(pk[i]) : "f"(v[q][2 * i + 1]), "f"(v[q][2 * i]));
        pk[i] += (pk[i] & 0x7FFF7FFFu) * 7;
      }
    }
    *reinterpret_cast<uint4*>(u + 6 * group_of(q, chunk) * UTILE) = make_uint4(pk[0], pk[1], pk[2], pk[3]);
    if (q == 3) *reinterpret_cast<uint4*>(u + 6 * group_of(5, chunk) * UTILE) = make_uint4(pk[0], pk[1], pk[2], pk[3]);
    if (q == 1 && last) made(ready, 1);
  }
  return m < 0.1875f;
}

__device__ __forceinline__ uint32_t smem_u32(const void* p) { return (uint32_t)__cvta_generic_to_shared(p); }
__device__ __forceinline__ void mbar_init(uint32_t bar, uint32_t cnt) {
  asm volatile("mbarrier.init.shared::cta.b64 [%0], %1;" ::"r"(bar), "r"(cnt));
}
__device__ __forceinline__ void mbar_expect_tx(uint32_t bar, uint32_t bytes) {
  asm volatile("mbarrier.arrive.expect_tx.shared::cta.b64 _, [%0], %1;" ::"r"(bar), "r"(bytes) : "memory");
}
__device__ __forceinline__ void mbar_wait(uint32_t bar, uint32_t parity) {
  asm volatile(
      "{\n.reg .pred p;\n"
      "WAIT_%=:\n"
      "mbarrier.try_wait.parity.shared::cta.b64 p, [%0], %1;\n"
      "@p bra DONE_%=;\n"
      "bra WAIT_%=;\n"
      "DONE_%=:\n}" ::"r"(bar), "r"(parity) : "memory");
}
__device__ __forceinline__ uint32_t mbar_try(uint32_t bar, uint32_t parity) {
  uint32_t ok;
  asm volatile(
      "{\n.reg .pred p;\n"
      "mbarrier.test_wait.parity.shared::cta.b64 p, [%1], %2;\n"
      "selp.u32 %0, 1, 0, p;\n}" : "=r"(ok) : "r"(bar), "r"(parity) : "memory");
  return ok;
}
__device__ __forceinline__ void mbar_wait_sleep(uint32_t bar, uint32_t parity) {
  asm volatile(
      "{\n.reg .pred p;\n"
      "WAIT_%=:\n"
      "mbarrier.try_wait.parity.shared::cta.b64 p, [%0], %1, 20000;\n"
      "@p bra DONE_%=;\n"
      "bra WAIT_%=;\n"
      "DONE_%=:\n}" ::"r"(bar), "r"(parity) : "memory");
}
#undef mbar_wait
#undef mbar_wait_sleep
__device__ __forceinline__ void arrive_elect(uint32_t bar) {
  asm volatile(
      "{\n.reg .pred p;\n"
      "elect.sync _|p, 0xffffffff;\n"
      "@p mbarrier.arrive.shared::cta.b64 _, [%0];\n}" ::"r"(bar) : "memory");
}
__device__ __forceinline__ void cluster_sync() {
  asm volatile("barrier.cluster.arrive.relaxed.aligned;\nbarrier.cluster.wait.aligned;" ::: "memory");
}
__device__ __forceinline__ void wg_fence() { asm volatile("wgmma.fence.sync.aligned;" ::: "memory"); }
__device__ __forceinline__ void wg_commit() { asm volatile("wgmma.commit_group.sync.aligned;" ::: "memory"); }
template <int N> __device__ __forceinline__ void wg_wait() { asm volatile("wgmma.wait_group.sync.aligned %0;" ::"n"(N) : "memory"); }
template <int LEAD>
__device__ __forceinline__ void wgmma192(uint32_t (&d)[48], uint64_t adesc, uint64_t bdesc, uint32_t acc) {
  asm volatile(
      "{\n.reg .pred p;\n"
      "setp.ne.b32 p, %50, 0;\n"
      "wgmma.mma_async.sync.aligned.m64n192k16.f16.f16.f16 "
      "{%0,%1,%2,%3,%4,%5,%6,%7,%8,%9,%10,%11,%12,%13,%14,%15,%16,%17,%18,%19,%20,%21,%22,%23,%24,%25,%26,%27,%28,%29,%30,%31,%32,%33,%34,%35,%36,%37,%38,%39,%40,%41,%42,%43,%44,%45,%46,%47}, %48, %49, p, 1, 1, 0, 0;\n}\n"
      : "+r"(d[0]),"+r"(d[1]),"+r"(d[2]),"+r"(d[3]),"+r"(d[4]),"+r"(d[5]),"+r"(d[6]),"+r"(d[7]),"+r"(d[8]),"+r"(d[9]),"+r"(d[10]),"+r"(d[11]),"+r"(d[12]),"+r"(d[13]),"+r"(d[14]),"+r"(d[15]),"+r"(d[16]),"+r"(d[17]),"+r"(d[18]),"+r"(d[19]),"+r"(d[20]),"+r"(d[21]),"+r"(d[22]),"+r"(d[23]),"+r"(d[24]),"+r"(d[25]),"+r"(d[26]),"+r"(d[27]),"+r"(d[28]),"+r"(d[29]),"+r"(d[30]),"+r"(d[31]),"+r"(d[32]),"+r"(d[33]),"+r"(d[34]),"+r"(d[35]),"+r"(d[36]),"+r"(d[37]),"+r"(d[38]),"+r"(d[39]),"+r"(d[40]),"+r"(d[41]),"+r"(d[42]),"+r"(d[43]),"+r"(d[44]),"+r"(d[45]),"+r"(d[46]),"+r"(d[47])
      : "l"(adesc), "l"(bdesc), "r"(LEAD ? acc : 1u));
}

__device__ __forceinline__ void sts(uint32_t addr, uint32_t v) { asm volatile("st.shared.u32 [%0], %1;" ::"r"(addr), "r"(v) : "memory"); }
__device__ __forceinline__ void sts(uint32_t addr, uint2 v) { asm volatile("st.shared.v2.u32 [%0], {%1,%2};" ::"r"(addr), "r"(v.x), "r"(v.y) : "memory"); }
__device__ __forceinline__ void lds(uint32_t& v, uint32_t addr) { asm volatile("ld.shared.u32 %0, [%1];" : "=r"(v) : "r"(addr) : "memory"); }
__device__ __forceinline__ void lds(uint2& v, uint32_t addr) { asm volatile("ld.shared.v2.u32 {%0,%1}, [%2];" : "=r"(v.x), "=r"(v.y) : "r"(addr) : "memory"); }
__host__ __device__ constexpr uint32_t h2(uint32_t h) { return h | (h << 16); }
constexpr uint32_t H_2 = h2(0x4000), H_1_2 = h2(0x3800), H_1_4 = h2(0x3400), H_1_8 = h2(0x3000), H_1_16 = h2(0x2C00), H_1_32 = h2(0x2800),
                   H_N4 = h2(0xC400), H_N2 = h2(0xC000), H_N1_2 = h2(0xB800), H_N1_4 = h2(0xB400), H_N17_4 = h2(0xC440), H_1 = h2(0x3C00), H_N1 = h2(0xBC00);
__device__ __forceinline__ uint32_t hfma(uint32_t a, uint32_t b, uint32_t c) {
  uint32_t r; asm("fma.rn.f16x2 %0, %1, %2, %3;" : "=r"(r) : "r"(a), "r"(b), "r"(c)); return r;
}
__device__ __forceinline__ uint32_t hadd(uint32_t a, uint32_t b) { uint32_t r; asm("add.rn.f16x2 %0, %1, %2;" : "=r"(r) : "r"(a), "r"(b)); return r; }
__device__ __forceinline__ uint32_t hsub(uint32_t a, uint32_t b) { uint32_t r; asm("sub.rn.f16x2 %0, %1, %2;" : "=r"(r) : "r"(a), "r"(b)); return r; }
__device__ __forceinline__ uint2 hfma(uint2 a, uint32_t b, uint2 c) { return make_uint2(hfma(a.x, b, c.x), hfma(a.y, b, c.y)); }
__device__ __forceinline__ uint2 hadd(uint2 a, uint2 b) { return make_uint2(hadd(a.x, b.x), hadd(a.y, b.y)); }
__device__ __forceinline__ uint2 hsub(uint2 a, uint2 b) { return make_uint2(hsub(a.x, b.x), hsub(a.y, b.y)); }
__device__ __forceinline__ uint32_t bmul(uint32_t x, uint32_t k) { uint32_t z; asm("mul.rn.bf16x2 %0, %1, %2;" : "=r"(z) : "r"(x), "r"(k)); return z; }
__device__ __forceinline__ void scale(uint32_t& x, uint32_t k, uint32_t& m) { x = bmul(x, k); m |= x; }
__device__ __forceinline__ void scale(uint2& x, uint32_t k, uint32_t& m) {
  x.x = bmul(x.x, k); x.y = bmul(x.y, k);
  asm("lop3.b32 %0, %0, %1, %2, 0xFE;" : "+r"(m) : "r"(x.x), "r"(x.y));
}
__device__ __forceinline__ void tohalf(uint32_t& z) { z = (z & 0x7FFF7FFFu) * 7 + z; }
__device__ __forceinline__ void tohalf(uint2& z) { tohalf(z.x); tohalf(z.y); }
__device__ __forceinline__ bool out_of_range(uint32_t m) {
  m = __reduce_or_sync(0xffffffffu, m & 0x7FFF7FFFu);
  return (m & 0x78007800u) || (m && !(m & 0x06000600u));
}

template <typename V>
__device__ __forceinline__ void planes8(V (&d)[8], uint32_t dp, uint32_t dq, uint32_t dr, uint32_t ds) {
  const V ec = hfma(d[4], H_N17_4, hadd(d[6], d[2])), oc = hfma(d[3], H_N17_4, hadd(d[5], d[1]));
  sts(dr, hadd(ec, oc)); sts(dr + TWG, hsub(ec, oc));
#pragma unroll
  for (int k = 0; k < 6; k++) d[k] = hsub(d[k + 2], d[k]);
  const V ea = hfma(d[2], H_N4, d[4]), oa = hfma(d[1], H_N4, d[3]);
  sts(dp, hfma(oa, H_1_2, ea)); sts(dq, hfma(oa, H_N1_2, ea));
  sts(ds, hfma(hfma(d[0], H_N4, d[2]), H_N1_4, ea)); sts(ds + TWG, hfma(oa, H_N1_4, hfma(d[3], H_N4, d[5])));
  const V eb = hfma(d[2], H_N1_4, d[4]), ob = hfma(d[1], H_N1_4, d[3]);
  sts(dp + TWG, hfma(ob, H_2, eb)); sts(dq + TWG, hfma(ob, H_N2, eb));
}
template <typename V>
__device__ __forceinline__ void planes4(V (&d)[8], uint32_t dp, uint32_t dq) {
  sts(dp, hadd(d[2], d[1])); sts(dp + TWG, hsub(d[2], d[1]));
  sts(dq, hsub(d[2], d[0])); sts(dq + TWG, hsub(d[3], d[1]));
}

constexpr uint32_t BHI = 256 >> 4, BLO = (128 >> 4) << 16, AHI = 128 >> 4, ALO = (TCOL >> 4) << 16;
__device__ __forceinline__ uint64_t desc(uint32_t lo, uint32_t hi) { uint64_t d; asm("mov.b64 %0, {%1,%2};" : "=l"(d) : "r"(lo), "r"(hi)); return d; }

typedef uint32_t Acc[48];
struct Ctx {
  uint32_t sb;
  uint64_t ad, bd;
  uint32_t b0;
  uint32_t me, ra, tx;
  uint32_t ok;
  bool one;
  uint32_t wg, xs, xr;
  uint32_t w[12];
  uint32_t k, sg;
  const char* o;
  bool on, yes;
};
__device__ __forceinline__ void arrive(uint32_t bar, bool on) {
  asm volatile("{\n.reg .pred p;\nsetp.ne.b32 p, %1, 0;\n@p mbarrier.arrive.shared::cta.b64 _, [%0];\n}" ::"r"(bar), "r"((uint32_t)on) : "memory");
}
template <int S>
__device__ __forceinline__ void release(Ctx& C, uint32_t me, uint32_t tx) {
  asm volatile(
      "{\n.reg .pred p;\n"
      "setp.ne.b32 p, %1, 0;\n"
      "@p mbarrier.arrive.expect_tx.shared::cta.b64 _, [%0], %1;\n}" ::"r"(C.b0 + 16 * S), "r"(tx) : "memory");
  asm volatile(
      "{\n.reg .pred p;\n"
      "setp.eq.b32 p, %0, %2;\n"
      "@p mbarrier.arrive.shared::cluster.b64 _, [%1];\n}" ::"r"(me), "r"(C.ra), "n"(S) : "memory");
}
template <int SYNC, int ID0, int ID1>
__device__ __forceinline__ void bar(uint32_t wg) {
  if (SYNC) asm volatile("{\n.reg .pred p;\nsetp.ne.b32 p, %0, 0;\n@!p bar.sync %1, 256;\n@p bar.sync %2, 256;\n}" ::"r"(wg), "n"(ID0), "n"(ID1) : "memory");
  else asm volatile("{\n.reg .pred p;\nsetp.ne.b32 p, %0, 0;\n@!p bar.arrive %1, 256;\n@p bar.arrive %2, 256;\n}" ::"r"(wg), "n"(ID0), "n"(ID1) : "memory");
}
__device__ __forceinline__ void sent(Ctx& C) { bar<0, 1, 2>(C.wg); }
__device__ __forceinline__ void await_sent(Ctx& C) { bar<1, 2, 1>(C.wg); }
__device__ __forceinline__ void sent2(Ctx& C) { bar<0, 10, 11>(C.wg); }
__device__ __forceinline__ void await_sent2(Ctx& C) { bar<1, 11, 10>(C.wg); }
__device__ __forceinline__ void await_taken(Ctx& C) { bar<1, 3, 4>(C.wg); }
__device__ __forceinline__ void taken(Ctx& C, uint32_t x) { if ((x & blockIdx.y) == 0) bar<0, 4, 3>(C.wg); }

__host__ __device__ constexpr int xoff(int u, int h) { return u * TUNIT + h * 2048; }
template <int B, int OF>
__device__ __forceinline__ void send(const Acc& A, uint32_t addr) {
  asm volatile("st.shared.v4.u32 [%4 + %5], {%0,%1,%2,%3};" ::"r"(A[4 * B]), "r"(A[4 * B + 1]), "r"(A[4 * B + 2]), "r"(A[4 * B + 3]), "r"(addr), "n"(OF) : "memory");
}
template <int B, int OF>
__device__ __forceinline__ void recv(Acc& A, uint32_t addr, bool on) {
  asm volatile("{\n.reg .pred p;\nsetp.ne.b32 p, %6, 0;\n@p ld.shared.v4.u32 {%0,%1,%2,%3}, [%4 + %5];\n}"
               : "+r"(A[4 * B]), "+r"(A[4 * B + 1]), "+r"(A[4 * B + 2]), "+r"(A[4 * B + 3]) : "r"(addr), "n"(OF), "r"((uint32_t)on) : "memory");
}
template <int OF>
__device__ __forceinline__ void fetch4(uint32_t* w, uint32_t addr) {
  asm volatile("ld.shared.v4.u32 {%0,%1,%2,%3}, [%4 + %5];" : "=r"(w[0]), "=r"(w[1]), "=r"(w[2]), "=r"(w[3]) : "r"(addr), "n"(OF) : "memory");
}
template <int I, int N>
__device__ __forceinline__ void add_to(Acc& A, const uint32_t* w, uint32_t sg) {
#pragma unroll
  for (int j = 0; j < N; j++) asm volatile("fma.rn.f16x2 %0, %1, %2, %0;" : "+r"(A[I + j]) : "r"(w[j]), "r"(sg));
}
template <int I, int N>
__device__ __forceinline__ void join(Acc& A, const Acc& B) {
#pragma unroll
  for (int j = I; j < I + N; j++) asm volatile("add.rn.f16x2 %0, %0, %1;" : "+r"(A[j]) : "r"(B[j]));
}
template <int B, int OF>
__device__ __forceinline__ void split(Acc& A, const Acc& Bb, uint32_t* w, uint32_t addr) {
#pragma unroll
  for (int j = 0; j < 4; j++)
    asm volatile("sub.rn.f16x2 %0, %1, %2;\nadd.rn.f16x2 %1, %1, %2;" : "=&r"(w[j]), "+r"(A[4 * B + j]) : "r"(Bb[4 * B + j]));
  asm volatile("st.shared.v4.u32 [%4 + %5], {%0,%1,%2,%3};" ::"r"(w[0]), "r"(w[1]), "r"(w[2]), "r"(w[3]), "r"(addr), "n"(OF) : "memory");
}
__host__ __device__ constexpr int pj(int k) { return 2 * (k >> 2) + (k & 1); }
__host__ __device__ constexpr int pp(int k) { return (k >> 1) & 1; }
template <int K>
__device__ __forceinline__ void rows(const Acc& P, Acc& Q, Acc& R, uint32_t* w) {
#pragma unroll
  for (int i = 0; i < 4; i++) {
    const int j = 8 * pj(K) + 2 * i + pp(K);
    asm volatile(
        "{\n.reg .b32 a, b;\n"
        "fma.rn.f16x2 a, %1, %4, %2;\n fma.rn.f16x2 b, %1, %5, %2;\n fma.rn.f16x2 %1, %1, %6, %2;\n"
        "fma.rn.f16x2 %0, %3, %7, a;\n fma.rn.f16x2 %2, %3, %8, b;\n add.rn.f16x2 %1, %1, %3;\n}"
        : "=r"(w[i]), "+r"(Q[j]), "+r"(R[j]) : "r"(P[j]), "r"(H_1_8), "r"(H_1_2), "r"(H_1_32), "r"(H_1_4), "r"(H_1_16));
  }
}
__device__ __forceinline__ uint32_t tobf(uint32_t h, uint32_t k) {
  uint32_t o;
  asm volatile("{\n.reg .b16 l, u;\n.reg .f32 a, b;\n.reg .b32 t;\nmov.b32 {l, u}, %1;\ncvt.f32.f16 a, l;\ncvt.f32.f16 b, u;\n"
               "cvt.rn.bf16x2.f32 t, b, a;\nmul.rn.bf16x2 %0, t, %2;\n}" : "=r"(o) : "r"(h), "r"(k));
  return o;
}
template <int K>
__device__ __forceinline__ void stg4(const char* o, const uint32_t* r) {
  asm volatile("st.global.cs.v4.u32 [%4 + %5], {%0,%1,%2,%3};" ::"r"(r[0]), "r"(r[1]), "r"(r[2]), "r"(r[3]), "l"(o), "n"(pp(K) * 8 * CH * 2 + pj(K) * 64) : "memory");
}
template <int K, int LAST = 0>
__device__ __forceinline__ void put(const Acc& A, Ctx& C) {
  uint32_t* w = C.w + (LAST ? 4 * (K & 1) : 8);
#pragma unroll
  for (int i = 0; i < 4; i++) w[i] = tobf(A[8 * pj(K) + 2 * i + pp(K)], C.k);
  stg4<K>(C.o, w);
}

constexpr uint64_t OUT_R = 0x252949290ull, OUT_S = 0x084210842108421ull, OUT_M = 0x151551540ull, OUT_F = 0x281015555ull;
constexpr int E0_AT = 6, E1_AT = 27;
__host__ __device__ constexpr int below(uint64_t m, int n) { return __builtin_popcountll(m & ((1ull << n) - 1)); }
static_assert(below(OUT_R, 36) == 12 && below(OUT_S, 60) == 12 && below(OUT_M, 35) == 12 && below(OUT_F, 36) == 12, "pieces");
static_assert(!(OUT_R & 15) && !(OUT_M & 0xC03F) && !(OUT_M & (OUT_M << 1)) && below(OUT_M, 8) <= 1 && below(OUT_M, 12) <= 4 && below(OUT_M, 24) <= 8 && below(OUT_M, 28) <= 9 && !(OUT_F & 0x7E000000) && E0_AT >= 6 && E1_AT >= 27, "order");

__host__ __device__ constexpr int r_out(int n) { return n >= 96 && n < 100 ? n - 96 : n == 124 || n == 125 ? n - 120 : -1; }
__host__ __device__ constexpr int d_out(int n) { return n >= 108 && n < 112 ? n - 108 : n == 122 || n == 123 ? n - 118 : -1; }
__host__ __device__ constexpr int r_in(int n) { return n >= 101 && n < 109 ? n - 101 : n == 130 || n == 131 ? n - 122 : n == 134 || n == 135 ? n - 124 : -1; }
__host__ __device__ constexpr int d_in(int n) { return n >= 112 && n < 120 ? n - 112 : n == 128 || n == 129 ? n - 120 : n == 132 || n == 133 ? n - 122 : -1; }
constexpr uint32_t XU_R = 0x750354, XU_D = 0x425421, XU_F = 0x984210;
template <int N, int FILL>
__device__ __forceinline__ void early(Acc& P, Acc& Q, Acc& R, Acc& S, Ctx& C) {
  if constexpr (FILL) {
    constexpr int I = N - 61;
    if constexpr (I == 0) await_sent(C);
    if constexpr (I >= 0 && I < 6) { fetch4<xoff(unit(XU_F, I), 0)>(C.w, C.xr); fetch4<xoff(unit(XU_F, I), 1)>(C.w + 4, C.xr); }
  } else {
    if constexpr (N == 101 || N == 116) await_sent(C);
    if constexpr (N == 112 || N == 128) await_sent2(C);
    if constexpr (r_in(N) >= 0) {
      constexpr int B = r_in(N);
      fetch4<xoff(unit(XU_R, B / 2), B & 1)>(C.w + 4, C.xr);
    }
    if constexpr (d_in(N) >= 0) recv<d_in(N), xoff(unit(XU_D, d_in(N) / 2), d_in(N) & 1)>(Q, C.xr, C.yes);
  }
}
template <int N, int FILL>
__device__ __forceinline__ void side(Acc& P, Acc& Q, Acc& R, Acc& S, Ctx& C) {
  const uint32_t te = C.sb + BAR_TEMPTY;
  if constexpr (FILL) {
    constexpr int I = N - 36, X = N - 54;
    if constexpr ((OUT_F >> I) & 1) { if (C.on) put<below(OUT_F, I)>(S, C); }
    if constexpr (X >= 0 && X < 6) { send<2 * X, xoff(unit(XU_F, X), 0)>(P, C.xs); send<2 * X + 1, xoff(unit(XU_F, X), 1)>(P, C.xs); }
    if constexpr (X == 5) sent(C);
    if constexpr (N == 66) { if (C.wg) asm volatile("bar.sync 6, 256;" ::: "memory"); }
    if constexpr (N == 71) { if (!C.wg) asm volatile("bar.arrive 6, 256;" ::: "memory"); }
    if constexpr (N >= 61 && N < 67) { if (C.yes) add_to<8 * (N - 61), 8>(P, C.w, C.sg); }
  } else if constexpr (N < 36) {
    if constexpr (N == 0) arrive(te + 16, C.one);
    if constexpr (N < 4) { if (C.on) join<12 * N, 12>(S, Q); }
    if constexpr ((OUT_R >> N) & 1) { if (C.on) put<below(OUT_R, N)>(R, C); }
    if constexpr (N == 30) arrive(te + 24, C.one);
  } else if constexpr (N < 96) {
    if constexpr ((OUT_S >> (N - 36)) & 1) { if (C.on) put<below(OUT_S, N - 36)>(S, C); }
    if constexpr (N == 48) arrive(te + 32, C.one);
    if constexpr (N == 72) arrive(te + 40, C.one);
  } else {
    constexpr int I = N - 108;
    if constexpr (I > 0) {
      if constexpr ((OUT_M >> (I - 1)) & 1) {
        if (C.yes) {
#pragma unroll
          for (int i = 0; i < 4; i++) C.w[8 + i] = tobf(C.w[i], C.k);
        }
        stg4<below(OUT_M, I - 1)>(C.o, C.w + 8);
      }
    }
    if constexpr (I >= 0) {
      if constexpr ((OUT_M >> I) & 1) { if (C.yes) rows<below(OUT_M, I)>(P, Q, R, C.w); }
    }
    if constexpr (N == 110 || N == 122) await_taken(C);
    if constexpr (r_out(N) >= 0) {
      constexpr int X = r_out(N);
      send<2 * X, xoff(unit(XU_R, X), 0)>(R, C.xs); send<2 * X + 1, xoff(unit(XU_R, X), 1)>(R, C.xs);
    }
    if constexpr (r_in(N) >= 0) {
      if (C.yes) {
        add_to<4 * r_in(N), 4>(R, C.w + 4, C.sg);
      }
    }
    if constexpr (d_out(N) >= 0) {
      constexpr int X = d_out(N);
      if (C.yes) { split<2 * X, xoff(unit(XU_D, X), 0)>(P, Q, C.w + 4, C.xs); split<2 * X + 1, xoff(unit(XU_D, X), 1)>(P, Q, C.w, C.xs); }
    }
    if constexpr (N == 99 || N == 111) sent(C);
    if constexpr (N == 109 || N == 125) sent2(C);
    if constexpr (N == 108) taken(C, R[31]);
    if constexpr (N == 120) taken(C, Q[11] | Q[15] | Q[19] | Q[23] | Q[27] | Q[31]);
    if constexpr (I == E0_AT) arrive(te, C.one && ((Q[3] | Q[7]) & blockIdx.y) == 0);
    if constexpr (I == E1_AT) arrive(te + 8, C.one && ((R[47] | Q[35] | Q[39] | Q[43] | Q[47]) & blockIdx.y) == 0);
  }
}
template <int W, int LEAD, int N0, int FILL, int J = 0>
__device__ __forceinline__ void group(Acc& P, Acc& Q, Acc& R, Acc& S, Ctx& C, uint64_t a) {
  constexpr int N = N0 + J;
  if (!C.ok) mbar_wait(C.b0 + 16 * (N % NUST), (N / NUST) & 1);
  wg_fence();
  wgmma192<LEAD && J == 0>(W == 0 ? P : W == 1 ? Q : W == 2 ? R : S, a + (((J / 3) * 2 * TCOL + (J % 3) * 16) >> 4), C.bd + (N % NUST) * (UTILE >> 4), blockIdx.y);
  wg_commit();
  C.ok = mbar_try(C.b0 + 16 * ((N + 1) % NUST), ((N + 1) / NUST) & 1);
  early<N, FILL>(P, Q, R, S, C);
  wg_wait<1>();
  if constexpr (!FILL || N + NUST <= 72) release<(N + NUST - 1) % NUST>(C, N || C.on ? C.me : 0, N || C.on ? C.tx : 0);
  side<N, FILL>(P, Q, R, S, C);
  if constexpr (J < 5) group<W, LEAD, N0, FILL, J + 1>(P, Q, R, S, C, a);
}

__device__ __forceinline__ void fetch(const CUtensorMap* map, uint32_t bytes, uint32_t dst, uint32_t bar, int c, int x, int y, uint64_t pol) {
  asm volatile("{\n.reg .pred p;\nelect.sync _|p, 0xffffffff;\n"
               "@p mbarrier.arrive.expect_tx.shared::cta.b64 _, [%2], %6;\n"
               "@p cp.async.bulk.tensor.3d.shared::cluster.global.mbarrier::complete_tx::bytes.L2::cache_hint [%0], [%1, {%3,%4,%5}], [%2], %7;\n}"
               ::"r"(dst), "l"(map), "r"(bar), "r"(c), "r"(x), "r"(y), "r"(bytes), "l"(pol) : "memory");
}
constexpr uint64_t POL_FIRST = 0x12F0000000000000ull, POL_SAME = 0x10F0000000000000ull;

struct Params { uint8_t* U; uint32_t* ready; int lg, mlg, ufirst, ustep, nunit, umax, nfill, s0, second, nfirst, nall; uint4 un[12]; };

__global__ void __launch_bounds__(NTHREADS, 1) wino_main(const __grid_constant__ CUtensorMap xmap8, const __grid_constant__ CUtensorMap xmap4,
                                                         const __grid_constant__ CUtensorMap xmap1, const __grid_constant__ CUtensorMap xmap0,
                                                         const __nv_bfloat16* __restrict__ xin, const __nv_bfloat16* __restrict__ wgt,
                                                         __nv_bfloat16* __restrict__ out, const Params P) {
  extern __shared__ __align__(1024) uint8_t smem[];
  { const uint32_t l = threadIdx.x * gridDim.x + blockIdx.x; if (l < 9 * CH * CH * 2 / 128) asm volatile("prefetch.global.L2 [%0];" ::"l"((const char*)wgt + l * 128u)); }
  const uint32_t sb = smem_u32(smem);
  const int warp = __shfl_sync(0xffffffffu, threadIdx.x >> 5, 0), lane = threadIdx.x & 31;
  const uint32_t cm = (1u << P.lg) - 1, rank = blockIdx.x & cm, mm = (1u << P.mlg) - 1, mrank = blockIdx.x & mm;
  const int cl = blockIdx.x >> P.lg;
  const int nit = min(P.umax, (P.nunit - cl * P.ufirst + P.ustep - 1) / P.ustep), fu = cl % P.nfill;
  auto first = [&](int i) {
    const int u = cl * P.ufirst + i * P.ustep, q = (u * (205 << (P.lg - 1))) >> 12;
    const int st = P.s0 + (i < nit ? q : fu >> (3 - P.lg));
    const int y = i < nit ? ((u - q * (40 >> P.lg)) * 6 << P.lg) + 6 * rank : 240 + ((fu & ((8 >> P.lg) - 1)) * 2 << P.lg) + 2 * rank;
    return (st & 7) * 64 + ((st >> 3) * 256 + y) * IMG;
  };

  auto origin = [&](int i) { int o; asm volatile("ld.shared.u32 %0, [%1];" : "=r"(o) : "r"(sb + SM_ORG + 4 * i)); return o; };
  if (warp == 11 && lane < 7) sts(sb + SM_ORG + 4 * lane, (uint32_t)first(min(lane, nit)));

  if (warp != 11) asm volatile("barrier.cluster.arrive.relaxed.aligned;" ::: "memory");
  if (warp == 10) {
    sts(sb + SM_EXP, min(sample_exp((const char*)wgt + lane * (4 * 5168), 5168), 240u));
    asm volatile("bar.arrive 11, 288;" ::: "memory");
  }
  if (warp == 9) {
    const uint32_t e = sample_exp((const char*)xin + ((uint32_t)(first(0) + 2 * lane + (lane & 1) * IMG) * (CH * 2u) + lane % 6 * 64), CH / 2 + 16);
    sts(sb + SM_EXP + 4, e ? min(e, 138u) : 120);
    asm volatile("bar.arrive 12, 192;\nbar.arrive 13, 288;" ::: "memory");
  }
  if (warp < 8) {
    const int t0 = warp * gridDim.x + blockIdx.x;
    if (P.second || t0 >= NFILT) { cluster_wait(); asm volatile("bar.sync 11, 288;" ::: "memory"); }
    if (!P.second) {
      bool ok = true;
      if (t0 >= NFILT) made(P.ready, 1);
#pragma unroll 1
      for (int t = t0; t < NFILT; t += 8 * gridDim.x) ok = filter_task(wgt, P.U, t, lane, sb + SM_EXP, t == t0, t + 8 * gridDim.x >= NFILT, P.ready) && ok;
      if (!ok) atomicOr(P.ready, 1u << 31);
      made(P.ready, 1024);
    }
  }
  if (warp == 8) {
    uint32_t v; asm volatile("ld.volatile.global.u32 %0, [%1];" : "=r"(v) : "l"(P.ready) : "memory");
    if (v < P.nfirst) __nanosleep(100);
  }
  if (threadIdx.x == 352) {
    for (int i = 0; i < 2 * NUST; i++) { mbar_init(sb + BAR_U + 16 * i, 1); mbar_init(sb + BAR_U + 16 * i + 8, mm + 1); }
    for (int i = 0; i < 6; i++) { mbar_init(sb + BAR_TFULL + 8 * i, 5); mbar_init(sb + BAR_TEMPTY + 8 * i, 8); }
    sts(sb + SM_FLAG, 0u);
    asm volatile("fence.mbarrier_init.release.cluster;" ::: "memory");
    for (int i = 0; i < 2 * NUST; i++) mbar_expect_tx(sb + BAR_U + 16 * i, UTILE);
  }
  const uint32_t rbar = __shfl_sync(0xffffffffu, sb + BAR_RFULL + (warp & 3) * 16, 0), rbuf = sb + SM_R + (warp & 3) * (2 * RSLOT);
  if (warp >= 12) {
    if (lane == 0) {
      mbar_init(rbar, 1); mbar_init(rbar + 8, 1);
      asm volatile("fence.mbarrier_init.release.cluster;" ::: "memory");
    }
    __syncwarp();
    if (!P.second) __nanosleep(300);
    const int o = first(0);
#pragma unroll
    for (int i = 0; i < 2; i++)
      fetch(nit ? &xmap0 : &xmap4, nit ? RSLOT : RSLOT / 2, rbuf + i * RSLOT, rbar + 8 * i, 0, (o & 511) - 1 + (warp & 3) * 16 + i * 4, (o >> 9) - 1, POL_SAME);
  }
  __syncwarp();
  if (warp == 11) asm volatile("barrier.cluster.arrive.relaxed.aligned;" ::: "memory");
  if (warp == 8 || warp > 10) cluster_wait();
  if (warp > 10) asm volatile("bar.sync 12, 192;" ::: "memory");
  if (warp < 8) asm volatile("bar.sync 13, 288;" ::: "memory");
  uint2 ex;
  lds(ex, sb + SM_EXP);
  const uint32_t kin = h2((139 - ex.y) << 7);

  if (warp >= 12) {
    asm volatile("setmaxnreg.dec.sync.aligned.u32 40;");
    const int wi = warp - 12;
    const uint32_t tb = __shfl_sync(0xffffffffu, sb + SM_T + ((lane >> 1) & 3) * TCOL + (wi * 16 + (lane >> 3)) * 16 + (lane & 1) * 8, lane);
    const uint32_t src = rbuf + __shfl_sync(0xffffffffu, lane * 8, lane);
    const uint32_t nb = __shfl_sync(0xffffffffu, lane & blockIdx.y, lane);
    int o = origin(0), x = (o & 511) - 1 + wi * 16, y = (o >> 9) - 1;
    uint32_t m = 0;
    auto chunk = [&](auto fill, int i, uint32_t c, int xn, int yn) {
      constexpr int NR = fill.value ? 4 : 8;
      const CUtensorMap* const map = fill.value ? &xmap4 : &xmap8;
      const uint4 un = P.un[6 * fill.value + c];
      const bool turn = c == 5, half = fill.value || (turn && i + 1 == nit);
      const CUtensorMap* const map1 = half ? &xmap4 : &xmap8;
      const int c1 = turn ? 0 : c * 32 + 32, x1 = turn ? xn : x, y1 = turn ? yn : y;
      const uint32_t n1 = half ? RSLOT / 2 : RSLOT;
#pragma unroll
      for (int q = 0; q < 4; q++) {
        const uint32_t sl = (q & 1) * RSLOT, rb = rbar + (q & 1) * 8;
        uint2 d[8];
        mbar_wait_sleep(rb, q >> 1);
#pragma unroll
        for (int r = 0; r < NR; r++) lds(d[r], src + sl + r * RROW);
#pragma unroll
        for (int r = 0; r < NR; r++) scale(d[r], kin, m);
        if (q < 2) fetch(!fill.value && i + c == 0 ? &xmap0 : map, NR * RROW | (m & nb), rbuf + sl, rb, c * 32, x + 8 + 4 * q, y, c & 1 ? POL_FIRST : POL_SAME);
        else if (!fill.value || !turn) fetch(map1, n1 | (m & nb), rbuf + sl, rb, c1, x1 + 4 * q - 8, y1, c & 1 ? POL_SAME : POL_FIRST);
#pragma unroll
        for (int r = 0; r < NR; r++) tohalf(d[r]);
        if (q == 0 && (!fill.value || c < 3)) mbar_wait_sleep(sb + BAR_TEMPTY + 8 * c, (i & 1) ^ (c < 2));
        if (q == 0 && wi == 0) TRACE(2, tn);
        const uint32_t t = tb + 64 * q;
        if (fill.value) planes4(d, t + un.x, t + un.y);
        else planes8(d, t + un.x, t + un.y, t + un.z, t + un.w);
      }
      if (turn) {
        if (out_of_range(m)) asm volatile("red.shared.or.b32 [%0], %1;" ::"r"(sb + SM_FLAG), "r"(1u << i) : "memory");
        m = 0; x = xn; y = yn;
      }
      asm volatile("fence.proxy.async.shared::cta;" ::: "memory");
      __syncwarp();
      arrive_elect(sb + BAR_TFULL + 8 * c);
    };
#pragma unroll 1
    for (int i = 0; i < nit; i++) {
      o = origin(i + 1);
#pragma unroll 1
      for (uint32_t c = 0; c < 6; c++) chunk(std::false_type(), i, c, (o & 511) - 1 + wi * 16, (o >> 9) - 1);
    }
#pragma unroll 1
    for (uint32_t c = 0; c < 6; c++) chunk(std::true_type(), nit, c, 0, 0);
    cluster_sync();
  } else if (warp >= 8) {
    asm volatile("setmaxnreg.dec.sync.aligned.u32 24;");
    if (warp < 10) {
      const uint32_t g = warp - 8, s0 = mrank ^ (13 * g & mm);
      const uint32_t ring = sb + SM_U + g * (NUST * UTILE), ub = sb + BAR_U + g * (NUST * 16);
      if (warp == 8) {
        uint32_t v, i = 0;
        do { asm volatile("ld.acquire.gpu.global.u32 %0, [%1];" : "=r"(v) : "l"(P.ready) : "memory"); if (++i > 5000000u) __trap(); } while ((v & 1023) < P.nfirst);
        asm volatile("bar.arrive 7, 64;" ::: "memory");
      }
      asm volatile("bar.sync 9, 64;" ::: "memory");
      asm volatile("fence.proxy.async.global;" ::: "memory");
      uint32_t ph = 1;
#pragma unroll 1
      for (int i = 0; i <= nit; i++) {
        const uint8_t* from = P.U + g * UWG + (i < nit ? 0 : NROUND * NUST * UTILE);
#pragma unroll 1
        for (uint32_t t = 0; t < (i < nit ? NROUND : NFROUND); t++, ph ^= 1, from += NUST * UTILE) {
          if (i == 0 && t == 36 / NUST) asm volatile("bar.sync 8, 96;\nfence.proxy.async.global;" ::: "memory");
#pragma unroll 1
          for (uint32_t s = s0; mm == 15 ? s < 9 : s < 8 || (s < 16 && s0 == (4 & mm)); s = s + mm + 1 < 8 ? s + mm + 1 : s < 8 && mm < 15 ? 8 : 16) {
            mbar_wait(ub + 16 * s + 8, ph);
            asm volatile(
                "{\n.reg .pred p;\n"
                "elect.sync _|p, 0xffffffff;\n"
                "@p cp.async.bulk.shared::cluster.global.mbarrier::complete_tx::bytes.multicast::cluster [%0], [%1], %2, [%4], %3;\n}"
                ::"r"(ring + s * UTILE), "l"(from + s * UTILE), "n"(UTILE), "h"((uint16_t)((2u << mm) - 1)), "r"(ub + 16 * s) : "memory");
          }
        }
      }
    } else if (warp == 10) {
      uint32_t v, i = 0;
      do { asm volatile("ld.acquire.gpu.global.u32 %0, [%1];" : "=r"(v) : "l"(P.ready) : "memory"); if (++i > 5000000u) __trap(); } while (((v >> 10) & 1023) < P.nfirst);
      if (v >> 31) asm volatile("red.shared.or.b32 [%0], %1;" ::"r"(sb + SM_FLAG), "r"(0xFFFFu) : "memory");
      __syncwarp();
      asm volatile("bar.arrive 8, 96;" ::: "memory");
      asm volatile("bar.sync 7, 64;" ::: "memory");
      if (lane == 0 && atomicAdd(P.ready + 32, 1) == P.nall - 1) P.ready[0] = P.ready[32] = 0;
      __syncwarp();
      asm volatile("griddepcontrol.launch_dependents;");
      auto ahead = [&](int i, uint32_t sl, int r) {
        const int o = origin(i), nr = i < nit ? 6 : 2;
        auto row = [&](int y) {
          asm volatile("{\n.reg .pred p;\nelect.sync _|p, 0xffffffff;\n@p cp.async.bulk.prefetch.tensor.3d.L2.global [%0, {%1,%2,%3}];\n}"
                       ::"l"(&xmap1), "r"(sl * 64), "r"((o & 511) - 1), "r"((o >> 9) + y) : "memory");
        };
        if (r < nr) row(r);
        if (r == 0 && rank == 0) row(-1);
        if (r + 1 == nr && rank == cm) row(nr);
      };
      uint32_t ph = 0;
#pragma unroll 1
      for (int i = 0; i <= nit; i++) {
#pragma unroll 1
        for (uint32_t t = 0; t < (i < nit ? NROUND : NFROUND - 3); t++, ph ^= 1) {
#pragma unroll 1
          for (int n = P.second ? 400 : 20; n && !mbar_try(sb + BAR_U + 16 * rank, ph); n--) __nanosleep(100);
          if (t - 1 < 6) ahead(i, 2, t - 1);
          if (i < nit && t - 6 < 6) ahead(i + 1, 0, t - 6);
          if (i < nit && t - 10 < 6) ahead(i + 1, 1, t - 10);
          if (((cl + t) & 7) == 0 && !P.second) {
            const uint32_t r = i == nit ? NROUND + t + 3 : t + 3 < NROUND || i + 1 == nit ? t + 3 : t + 3 - NROUND;
            if (lane < (rank == 4 ? 4 : 2))
              asm volatile("cp.async.bulk.prefetch.L2.global [%0], %1;" ::"l"(P.U + ((lane & 1) * UWG + (r * NUST + (lane >> 1 ? 8 : rank)) * UTILE)), "n"(UTILE) : "memory");
            __syncwarp();
          }
        }
      }
    } else {
      const uint32_t tb = sb + SM_T + ((lane >> 2) & 3) * TCOL + (64 + (lane >> 4)) * 16 + (lane & 3) * 4;
      uint32_t iph = 0;
#pragma unroll 1
      for (int i = 0; i <= nit; i++, iph ^= 1) {
        const int o = origin(i), x = (o & 511) + 63 + (lane >> 4), y = (o >> 9) - 1, nr = i < nit ? 8 : 4;
        const char* p = (const char*)xin + (uint32_t)(o + 63 + (lane >> 4)) * (CH * 2u) + (lane & 15) * 4;
        uint32_t m = 0;
#pragma unroll 1
        for (uint32_t c = 0; c < 6; c++, p += 64) {
          uint32_t d[8];
#pragma unroll
          for (int r = 0; r < 8; r++) {
            d[r] = 0;
            if (x < IMG && (uint32_t)(y + r) < IMG && r < nr) asm volatile("ld.global.nc.u32 %0, [%1];" : "=r"(d[r]) : "l"(p + (r - 1) * ROWB));
          }
#pragma unroll
          for (int r = 0; r < 8; r++) { scale(d[r], kin, m); tohalf(d[r]); }
          if (i < nit || c < 3) mbar_wait_sleep(sb + BAR_TEMPTY + 8 * c, iph ^ (c < 2));
          if (i < nit) planes8(d, tb + unit(UN_P, c) * TUNIT, tb + unit(UN_Q, c) * TUNIT, tb + unit(UN_R, c) * TUNIT, tb + unit(UN_S, c) * TUNIT);
          else planes4(d, tb + unit(UN_FP, c) * TUNIT, tb + unit(UN_FQ, c) * TUNIT);
          if (c == 5 && (m & 0x78007800u)) asm volatile("red.shared.or.b32 [%0], %1;" ::"r"(sb + SM_FLAG), "r"(1u << i) : "memory");
          asm volatile("fence.proxy.async.shared::cta;" ::: "memory");
          __syncwarp();
          arrive_elect(sb + BAR_TFULL + 8 * c);
        }
      }
      if (P.second == 2) asm volatile("griddepcontrol.wait;" ::: "memory");
    }
    __syncwarp();
    cluster_sync();
  } else {
    const uint32_t ek = ex.x ? ex.x + ex.y - 119 : 0;
    asm volatile("setmaxnreg.inc.sync.aligned.u32 224;");
    const int wg = warp >> 2;
    Ctx C;
    C.sb = sb; C.wg = wg;
    C.b0 = sb + BAR_U + wg * (NUST * 16);
    C.bd = desc(BLO + (((sb + SM_U + wg * (NUST * UTILE)) & 0x3FFFF) >> 4), BHI);
    C.ad = desc(ALO + (((sb + SM_T + wg * TWG) & 0x3FFFF) >> 4), AHI);
    C.me = __shfl_sync(0xffffffffu, threadIdx.x & 127, lane); C.tx = __shfl_sync(0xffffffffu, (threadIdx.x & 127) == 0 ? UTILE : 0, lane);
    asm volatile("mapa.shared::cluster.u32 %0, %1, %2;" : "=r"(C.ra) : "r"(C.b0 + 16 * lane + 8), "r"(((lane == 8 && mm < 15 ? 4 : lane) ^ 13 * wg) & mm));
    C.ok = 0;
    const uint32_t t16 = __shfl_sync(0xffffffffu, (warp & 3) * 512 + lane * 16, lane);
    C.one = (t16 & 511) == 0;
    C.xs = sb + SM_T + wg * TWG + t16;
    C.xr = sb + SM_T + (wg ^ 1) * TWG + t16;
    C.k = h2(ek << 7); C.sg = wg ? H_1 : H_N1;
    C.yes = C.sb != gridDim.x;
    const int drow = wg ? -2 * ROWB : 2 * ROWB;
    const char* const ob = (const char*)out + (uint32_t)(((warp & 3) * 16 + (lane >> 2)) * CH + (lane & 3) * 8) * 2u;
    C.o = ob;
#pragma unroll
    for (int i = 0; i < 12; i++) C.w[i] = 0;

    Acc A0, A1, A2, A3;
#pragma unroll
    for (int j = 0; j < 48; j++) { A0[j] = 0; A1[j] = 0; A2[j] = 0; A3[j] = 0; }
#define G(W, LEAD, N0, FILL, U) group<W, LEAD, N0, FILL>(A0, A1, A2, A3, C, C.ad + (U) * (TUNIT >> 4))
    uint32_t ph = 0;
#pragma unroll 1
    for (int item = 0;; item++) {
      C.on = item != 0;
      if (P.second && item == 2) {
        const int wait = (5 - nit) * 28000 - 16000;
        uint32_t c0, c;
        asm volatile("mov.u32 %0, %%clock;" : "=r"(c0));
        do { __nanosleep(500); asm volatile("mov.u32 %0, %%clock;" : "=r"(c)); } while ((int)(c - c0) < wait);
      }
      C.ad += item & blockIdx.y; C.bd += item & blockIdx.y;
      mbar_wait(sb + BAR_TFULL, ph);
      G(0, 1, 0, 0, unit(UN_P, 0));
      G(1, 1, 6, 0, unit(UN_Q, 0));
      mbar_wait(sb + BAR_TFULL + 8, ph);
      G(0, 0, 12, 0, unit(UN_P, 1)); G(1, 0, 18, 0, unit(UN_Q, 1));
      mbar_wait(sb + BAR_TFULL + 16, ph);
      G(0, 0, 24, 0, unit(UN_P, 2)); G(1, 0, 30, 0, unit(UN_Q, 2));
      C.o -= 2 * drow;
      if (item == nit) break;
      G(2, 1, 36, 0, unit(UN_R, 0)); G(2, 0, 42, 0, unit(UN_R, 1)); G(2, 0, 48, 0, unit(UN_R, 2));
      mbar_wait(sb + BAR_TFULL + 24, ph);
      G(2, 0, 54, 0, unit(UN_R, 3)); G(0, 0, 60, 0, unit(UN_P, 3)); G(1, 0, 66, 0, unit(UN_Q, 3));
      mbar_wait(sb + BAR_TFULL + 32, ph);
      G(2, 0, 72, 0, unit(UN_R, 4)); G(0, 0, 78, 0, unit(UN_P, 4)); G(1, 0, 84, 0, unit(UN_Q, 4));
      mbar_wait(sb + BAR_TFULL + 40, ph);
      G(2, 0, 90, 0, unit(UN_R, 5)); G(0, 0, 96, 0, unit(UN_P, 5)); G(1, 0, 102, 0, unit(UN_Q, 5));
      ph ^= 1;
      C.o = ob + (uint32_t)(origin(item) + (2 + wg) * IMG) * (CH * 2u);
      G(3, 1, 108, 0, unit(UN_S, 0)); G(3, 0, 114, 0, unit(UN_S, 1)); G(3, 0, 120, 0, unit(UN_S, 2));
      G(3, 0, 126, 0, unit(UN_S, 3)); G(3, 0, 132, 0, unit(UN_S, 4)); G(3, 0, 138, 0, unit(UN_S, 5));
      C.o += drow;
    }
    mbar_wait(sb + BAR_TFULL + 24, ph);
    G(0, 0, 36, 1, unit(UN_FP, 3));
    mbar_wait(sb + BAR_TFULL + 32, ph);
    G(0, 0, 42, 1, unit(UN_FP, 4));
    mbar_wait(sb + BAR_TFULL + 40, ph);
    G(0, 0, 48, 1, unit(UN_FP, 5));
    G(1, 0, 54, 1, unit(UN_FQ, 3)); G(1, 0, 60, 1, unit(UN_FQ, 4)); G(1, 0, 66, 1, unit(UN_FQ, 5));
#undef G
    wg_wait<0>();
    asm volatile("barrier.cluster.arrive.relaxed.aligned;" ::: "memory");
    uint32_t redo;
    asm volatile("ld.shared.u32 %0, [%1];" : "=r"(redo) : "r"(sb + SM_FLAG) : "memory");
    if (cl < P.nfill) {
      C.o = ob + (uint32_t)(origin(nit) + wg * IMG) * (CH * 2u);
      join<0, 48>(A1, A0);
      put<0, 1>(A1, C); put<1, 1>(A1, C); put<2, 1>(A1, C); put<3, 1>(A1, C); put<4, 1>(A1, C); put<5, 1>(A1, C);
      put<6, 1>(A1, C); put<7, 1>(A1, C); put<8, 1>(A1, C); put<9, 1>(A1, C); put<10, 1>(A1, C); put<11, 1>(A1, C);
    }
    if (ek - 1 > 253) redo = 0xFFFF;
    if (redo) {
      asm volatile("bar.sync 5, 256;" ::: "memory");
      const int k = threadIdx.x;
#pragma unroll 1
      for (int i = 0; i < nit + (cl < P.nfill); i++) {
        if (!((redo >> i) & 1) || k >= CH) continue;
        const int o = origin(i);
#pragma unroll 1
        for (int t = 0; t < (i < nit ? 48 : 16); t++) {
          const int y = (o >> 9) + (t >> 3), x = (o & 511) + (t & 7) * 8;
          float acc[8];
#pragma unroll
          for (int j = 0; j < 8; j++) acc[j] = 0.f;
#pragma unroll 1
          for (int rs = 0; rs < 9; rs++) {
            const int yy = y + rs / 3 - 1, xx = x + rs % 3 - 1;
            if ((uint32_t)yy >= IMG) continue;
#pragma unroll 1
            for (int c = 0; c < CH; c += 2) {
              const float w0 = __bfloat162float(wgt[(rs * CH + c) * CH + k]), w1 = __bfloat162float(wgt[(rs * CH + c + 1) * CH + k]);
#pragma unroll
              for (int j = 0; j < 8; j++) {
                if ((uint32_t)(xx + j) < IMG) {
                  const uint32_t v = __ldg(reinterpret_cast<const uint32_t*>(xin + (yy * IMG + xx + j) * CH + c));
                  acc[j] = fmaf(__uint_as_float(v & 0xFFFF0000u), w1, fmaf(__uint_as_float(v << 16), w0, acc[j]));
                }
              }
            }
          }
#pragma unroll
          for (int j = 0; j < 8; j++) out[(y * IMG + x + j) * CH + k] = __float2bfloat16(acc[j]);
        }
      }
    }
    __syncwarp();
    asm volatile("barrier.cluster.wait.aligned;" ::: "memory");
  }
}

typedef CUresult (*EncFn)(CUtensorMap*, CUtensorMapDataType, cuuint32_t, void*, const cuuint64_t*, const cuuint64_t*,
                          const cuuint32_t*, const cuuint32_t*, CUtensorMapInterleave, CUtensorMapSwizzle,
                          CUtensorMapL2promotion, CUtensorMapFloatOOBfill);

}

extern "C" void kernel_launch(void* const* d_in, const int* in_sizes, int n_in, void* d_out, int out_size) {
  const __nv_bfloat16* x = (const __nv_bfloat16*)d_in[0];
  const __nv_bfloat16* w = (const __nv_bfloat16*)d_in[1];
  __nv_bfloat16* out = (__nv_bfloat16*)d_out;

  static EncFn enc = nullptr;
  static void *U = nullptr, *ready = nullptr;
  if (!enc) {
    cudaGetSymbolAddress(&U, g_U);
    cudaGetSymbolAddress(&ready, g_ready);
    void* fn = nullptr; cudaDriverEntryPointQueryResult st;
    cudaGetDriverEntryPoint("cuTensorMapEncodeTiled", &fn, cudaEnableDefault, &st);
    enc = (EncFn)fn;
    cudaFuncSetAttribute(wino_main, cudaFuncAttributeMaxDynamicSharedMemorySize, SMEM_BYTES);
    cudaFuncSetAttribute(wino_main, cudaFuncAttributeNonPortableClusterSizeAllowed, 1);
  }
  CUtensorMap xmap[4];
  for (int i = 0; i < 4; i++) {
    cuuint64_t dims[3] = {CH, IMG, IMG};
    cuuint64_t str[2] = {CH * 2, (cuuint64_t)ROWB};
    cuuint32_t box[3] = {i != 2 ? 32u : 64u, i != 2 ? 4u : 66u, i == 2 ? 1u : i == 1 ? 4u : 8u};
    cuuint32_t es[3] = {1, 1, 1};
    enc(&xmap[i], CU_TENSOR_MAP_DATA_TYPE_BFLOAT16, 3, (void*)x, dims, str, box, es, CU_TENSOR_MAP_INTERLEAVE_NONE,
        CU_TENSOR_MAP_SWIZZLE_NONE, i == 3 ? CU_TENSOR_MAP_L2_PROMOTION_NONE : CU_TENSOR_MAP_L2_PROMOTION_L2_128B, CU_TENSOR_MAP_FLOAT_OOB_FILL_NONE);
  }
  cudaLaunchConfig_t cfg = {};
  cudaLaunchAttribute attr[2];
  cfg.blockDim = dim3(NTHREADS);
  cfg.dynamicSmemBytes = SMEM_BYTES;
  cfg.stream = cudaStreamPerThread;
  attr[0].id = cudaLaunchAttributeClusterDimension;
  attr[0].val.clusterDim.x = 16; attr[0].val.clusterDim.y = 1; attr[0].val.clusterDim.z = 1;
  attr[1].id = cudaLaunchAttributeProgrammaticStreamSerialization;
  attr[1].val.programmaticStreamSerializationAllowed = 1;
  cfg.attrs = attr;
  static int mlg = 0, ns = 0, n2 = 0;
  if (!mlg) {
    cfg.numAttrs = 1;
    cfg.gridDim = dim3(128);
    int n[3] = {0, 0, 0};
    for (int i = 0; i < 3; i++) {
      attr[0].val.clusterDim.x = i == 2 ? 2 : 16 >> i;
      if (cudaOccupancyMaxActiveClusters(&n[i], wino_main, &cfg) != cudaSuccess) { n[i] = 0; cudaGetLastError(); }
    }
    mlg = n[0] >= 7 ? 4 : 3;
    ns = mlg == 4 ? 2 * n[0] : n[1];
    ns = ns < 1 ? 1 : ns > 16 ? 16 : ns;
    n2 = n[2] - 4 * ns;
  }
  const int nf = 4 * (16 - ns), nb = n2 < nf ? nf : n2 > 5 * nf ? 5 * nf : n2;
  Params P = {(uint8_t*)U, (uint32_t*)ready, 3, mlg, 5, 1, 5 * ns, 5, ns, 0, 0, 8 * ns, 8 * ns + 2 * nb};
  for (int c = 0; c < 6; c++) {
    P.un[c] = make_uint4(unit(UN_P, c) * TUNIT, unit(UN_Q, c) * TUNIT, unit(UN_R, c) * TUNIT, unit(UN_S, c) * TUNIT);
    P.un[6 + c] = make_uint4(unit(UN_FP, c) * TUNIT, unit(UN_FQ, c) * TUNIT, 0, 0);
  }
  attr[0].val.clusterDim.x = 1 << mlg;
  cfg.numAttrs = 1;
  cfg.gridDim = dim3(8 * ns);
  cudaLaunchKernelEx(&cfg, wino_main, xmap[0], xmap[1], xmap[2], xmap[3], x, w, out, P);
  if (!nb) return;
  cudaStreamCaptureStatus cap = cudaStreamCaptureStatusNone;
  cudaStreamIsCapturing(cfg.stream, &cap);
  P.lg = P.mlg = 1; P.ufirst = 1; P.ustep = nb; P.nunit = 5 * nf; P.nfill = nf; P.s0 = ns; P.second = cap == cudaStreamCaptureStatusActive ? 1 : 2;
  attr[0].val.clusterDim.x = 2;
  cfg.numAttrs = 2;
  cfg.gridDim = dim3(2 * nb);
  cudaLaunchKernelEx(&cfg, wino_main, xmap[0], xmap[1], xmap[2], xmap[3], x, w, out, P);
}
```

```cpp
#include <cuda_runtime.h>
#include <cuda.h>
#include <cuda_bf16.h>
#include <stdint.h>
#include <type_traits>

namespace {

constexpr int IMG = 512;
constexpr int CH = 192;
constexpr int ROWB = IMG * CH * 2;
constexpr int TCOL = 66 * 16;
constexpr int TUNIT = 4 * TCOL;
constexpr int TWG = 12 * TUNIT;
constexpr int RROW = 4 * 64;
constexpr int RSLOT = 8 * RROW;
constexpr int UTILE = 192 * 32;
constexpr int NUST = 9;
constexpr int NROUND = 144 / NUST, NFROUND = 72 / NUST;
constexpr int UWG = (NROUND + NFROUND) * NUST * UTILE;
constexpr int SM_U = 0;
constexpr int SM_R = SM_U + 2 * NUST * UTILE;
constexpr int SM_T = 131072 - 1024;
constexpr int SM_BAR = SM_T + 2 * TWG;
static_assert(SM_R + 4 * 2 * RSLOT <= SM_T, "smem");
constexpr int SMEM_BYTES = SM_BAR + 256 + 32 * NUST + 16;
constexpr int NTHREADS = 512;
constexpr uint32_t BAR_TFULL = SM_BAR, BAR_TEMPTY = SM_BAR + 48, SM_FLAG = SM_BAR + 96, SM_ORG = SM_BAR + 100, SM_EXP = SM_BAR + 256 + 32 * NUST, BAR_RFULL = SM_BAR + 128,
                   BAR_U = SM_BAR + 256;
static_assert(SMEM_BYTES <= 232448 && SM_R % 128 == 0, "smem");

__host__ __device__ constexpr int group_of(int q, int c) {
  return q == 0 ? (c < 3 ? 2 * c : 3 * c + 1) : q == 1 ? (c < 3 ? 2 * c + 1 : 3 * c + 2) : q == 2 ? (c < 3 ? 6 + c : 3 * c) : q == 3 ? 18 + c
       : q == 4 ? 24 + (c < 3 ? 2 * c : 3 + c) : 24 + (c < 3 ? 2 * c + 1 : 6 + c);
}
constexpr uint32_t UN_P = 0x141820, UN_Q = 0x252941, UN_R = 0x030A53, UN_S = 0xA98B76, UN_FP = 0xA53820, UN_FQ = 0xB76941;
__host__ __device__ constexpr uint32_t unit(uint32_t tab, int c) { return (tab >> (4 * c)) & 15; }

__device__ __align__(1024) uint8_t g_U[2 * UWG];
__device__ uint32_t g_ready[64];
#define TRACE(row, i)

__device__ __forceinline__ void cluster_wait() { asm volatile("barrier.cluster.wait.acquire.aligned;" ::: "memory"); }
__device__ __forceinline__ uint32_t sample_exp(const char* p, uint32_t stride) {
  uint32_t m = 0;
  uint4 v[4];
#pragma unroll
  for (int i = 0; i < 4; i++)
    asm volatile("ld.global.nc.v4.u32 {%0,%1,%2,%3}, [%4];" : "=r"(v[i].x), "=r"(v[i].y), "=r"(v[i].z), "=r"(v[i].w) : "l"(p + i * stride));
  cluster_wait();
#pragma unroll
  for (int i = 0; i < 4; i++)
    m = __vmaxu2(__vmaxu2(m, __vmaxu2(v[i].x & 0x7FFF7FFFu, v[i].y & 0x7FFF7FFFu)), __vmaxu2(v[i].z & 0x7FFF7FFFu, v[i].w & 0x7FFF7FFFu));
  return __reduce_max_sync(0xffffffffu, max(m & 0xFFFFu, m >> 16)) >> 7;
}

constexpr int PQBITS = 9;
constexpr int NFILT = 2 * 6 * 24 * 3;
__device__ __forceinline__ void made(uint32_t* ready, uint32_t n) {
  asm volatile("fence.proxy.async.global;\nbar.sync 10, 256;" ::: "memory");
  if (threadIdx.x == 0) asm volatile("red.release.gpu.global.add.u32 [%0], %1;" ::"l"(ready), "r"(n) : "memory");
  __syncwarp();
}
__device__ __forceinline__ bool filter_task(const __nv_bfloat16* __restrict__ w, uint8_t* U, int t, int lane, uint32_t ew, bool first, bool last, uint32_t* ready) {
  const int wg = t & 1, blk = (t >> 1) % 6, co = (t / 12) % 24, s = t / (12 * 24);
  const int k = blk * 32 + ((lane >> 1) & 3) * 8 + (lane >> 3) * 2 + (lane & 1);
  const unsigned short* wp = reinterpret_cast<const unsigned short*>(w) + ((wg * 6 + s) * CH + co * 8) * CH + k;
  const int dr = wg ? -3 * CH * CH : 3 * CH * CH;
  uint32_t g[3][8];
#pragma unroll
  for (int r = 0; r < 3; r++)
#pragma unroll
    for (int i = 0; i < 8; i++) asm volatile("ld.global.nc.u16 %0, [%1];" : "=r"(g[r][i]) : "l"(wp + r * dr + i * CH));
  const int chunk = co >> 2;
  uint8_t* const u = U + wg * UWG + (3 * ((co >> 1) & 1) + s) * UTILE + (blk * 4 + (lane >> 3)) * 256 + (co & 1) * 128 + (lane & 7) * 16;
  if (first) { cluster_wait(); asm volatile("bar.sync 11, 288;" ::: "memory"); }
  asm volatile("ld.shared.u32 %0, [%0];" : "+r"(ew)::"memory");
  const float su = __uint_as_float((249 - ew) << 23), low = __uint_as_float(15u << 23);
  const float na = wg ? 128.f / 90.f : 1.f / 1.40625f, sg = wg ? -1.f : 1.f;
  float v[5][8], m = 0.f;
#pragma unroll
  for (int i = 0; i < 8; i++) {
    const float a = __uint_as_float(g[0][i] << 16) * su, b = __uint_as_float(g[1][i] << 16) * su, c = __uint_as_float(g[2][i] << 16) * su;
    asm("{\n.reg .f32 t;\nmax.NaN.f32 t, %1, %2;\nmax.NaN.f32 %0, %0, %3;\nmax.NaN.f32 %0, %0, t;\n}" : "+f"(m) : "f"(fabsf(a)), "f"(fabsf(b)), "f"(fabsf(c)));
    const float e = fmaf(0.25f, c, a) * na, o = b * (0.5f * na), d = fmaf(a + c, sg, b);
    v[0][i] = e + o; v[1][i] = (e - o) * sg; v[2][i] = d * (low / -4.5f); v[3][i] = a * (-sg * low); v[4][i] = d * (0.5f * low);
  }
#pragma unroll
  for (int q = 0; q < 5; q++) {
    uint32_t pk[4];
#pragma unroll
    for (int i = 0; i < 4; i++) {
      if (q < 2) {
        asm("cvt.rz.f16x2.f32 %0, %1, %2;" : "=r"(pk[i]) : "f"(v[q][2 * i + 1]), "f"(v[q][2 * i]));
        pk[i] = (pk[i] + (0x00010001u << (10 - PQBITS))) & ~((0x00010001u << (11 - PQBITS)) - 0x00010001u);
      } else {
        asm("cvt.rn.bf16x2.f32 %0, %1, %2;" : "=r"(pk[i]) : "f"(v[q][2 * i + 1]), "f"(v[q][2 * i]));
        pk[i] += (pk[i] & 0x7FFF7FFFu) * 7;
      }
    }
    *reinterpret_cast<uint4*>(u + 6 * group_of(q, chunk) * UTILE) = make_uint4(pk[0], pk[1], pk[2], pk[3]);
    if (q == 3) *reinterpret_cast<uint4*>(u + 6 * group_of(5, chunk) * UTILE) = make_uint4(pk[0], pk[1], pk[2], pk[3]);
    if (q == 1 && last) made(ready, 1);
  }
  return m < 0.1875f;
}

__device__ __forceinline__ uint32_t smem_u32(const void* p) { return (uint32_t)__cvta_generic_to_shared(p); }
__device__ __forceinline__ void mbar_init(uint32_t bar, uint32_t cnt) {
  asm volatile("mbarrier.init.shared::cta.b64 [%0], %1;" ::"r"(bar), "r"(cnt));
}
__device__ __forceinline__ void mbar_expect_tx(uint32_t bar, uint32_t bytes) {
  asm volatile("mbarrier.arrive.expect_tx.shared::cta.b64 _, [%0], %1;" ::"r"(bar), "r"(bytes) : "memory");
}
__device__ __forceinline__ void mbar_wait(uint32_t bar, uint32_t parity) {
  asm volatile(
      "{\n.reg .pred p;\n"
      "WAIT_%=:\n"
      "mbarrier.try_wait.parity.shared::cta.b64 p, [%0], %1;\n"
      "@p bra DONE_%=;\n"
      "bra WAIT_%=;\n"
      "DONE_%=:\n}" ::"r"(bar), "r"(parity) : "memory");
}
__device__ __forceinline__ uint32_t mbar_try(uint32_t bar, uint32_t parity) {
  uint32_t ok;
  asm volatile(
      "{\n.reg .pred p;\n"
      "mbarrier.test_wait.parity.shared::cta.b64 p, [%1], %2;\n"
      "selp.u32 %0, 1, 0, p;\n}" : "=r"(ok) : "r"(bar), "r"(parity) : "memory");
  return ok;
}
__device__ __forceinline__ void mbar_wait_sleep(uint32_t bar, uint32_t parity) {
  asm volatile(
      "{\n.reg .pred p;\n"
      "WAIT_%=:\n"
      "mbarrier.try_wait.parity.shared::cta.b64 p, [%0], %1, 20000;\n"
      "@p bra DONE_%=;\n"
      "bra WAIT_%=;\n"
      "DONE_%=:\n}" ::"r"(bar), "r"(parity) : "memory");
}
#undef mbar_wait
#undef mbar_wait_sleep
__device__ __forceinline__ void arrive_elect(uint32_t bar) {
  asm volatile(
      "{\n.reg .pred p;\n"
      "elect.sync _|p, 0xffffffff;\n"
      "@p mbarrier.arrive.shared::cta.b64 _, [%0];\n}" ::"r"(bar) : "memory");
}
__device__ __forceinline__ void cluster_sync() {
  asm volatile("barrier.cluster.arrive.relaxed.aligned;\nbarrier.cluster.wait.aligned;" ::: "memory");
}
__device__ __forceinline__ void wg_fence() { asm volatile("wgmma.fence.sync.aligned;" ::: "memory"); }
__device__ __forceinline__ void wg_commit() { asm volatile("wgmma.commit_group.sync.aligned;" ::: "memory"); }
template <int N> __device__ __forceinline__ void wg_wait() { asm volatile("wgmma.wait_group.sync.aligned %0;" ::"n"(N) : "memory"); }
template <int LEAD>
__device__ __forceinline__ void wgmma192(uint32_t (&d)[48], uint64_t adesc, uint64_t bdesc, uint32_t acc) {
  asm volatile(
      "{\n.reg .pred p;\n"
      "setp.ne.b32 p, %50, 0;\n"
      "wgmma.mma_async.sync.aligned.m64n192k16.f16.f16.f16 "
      "{%0,%1,%2,%3,%4,%5,%6,%7,%8,%9,%10,%11,%12,%13,%14,%15,%16,%17,%18,%19,%20,%21,%22,%23,%24,%25,%26,%27,%28,%29,%30,%31,%32,%33,%34,%35,%36,%37,%38,%39,%40,%41,%42,%43,%44,%45,%46,%47}, %48, %49, p, 1, 1, 0, 0;\n}\n"
      : "+r"(d[0]),"+r"(d[1]),"+r"(d[2]),"+r"(d[3]),"+r"(d[4]),"+r"(d[5]),"+r"(d[6]),"+r"(d[7]),"+r"(d[8]),"+r"(d[9]),"+r"(d[10]),"+r"(d[11]),"+r"(d[12]),"+r"(d[13]),"+r"(d[14]),"+r"(d[15]),"+r"(d[16]),"+r"(d[17]),"+r"(d[18]),"+r"(d[19]),"+r"(d[20]),"+r"(d[21]),"+r"(d[22]),"+r"(d[23]),"+r"(d[24]),"+r"(d[25]),"+r"(d[26]),"+r"(d[27]),"+r"(d[28]),"+r"(d[29]),"+r"(d[30]),"+r"(d[31]),"+r"(d[32]),"+r"(d[33]),"+r"(d[34]),"+r"(d[35]),"+r"(d[36]),"+r"(d[37]),"+r"(d[38]),"+r"(d[39]),"+r"(d[40]),"+r"(d[41]),"+r"(d[42]),"+r"(d[43]),"+r"(d[44]),"+r"(d[45]),"+r"(d[46]),"+r"(d[47])
      : "l"(adesc), "l"(bdesc), "r"(LEAD ? acc : 1u));
}

__device__ __forceinline__ void sts(uint32_t addr, uint32_t v) { asm volatile("st.shared.u32 [%0], %1;" ::"r"(addr), "r"(v) : "memory"); }
__device__ __forceinline__ void sts(uint32_t addr, uint2 v) { asm volatile("st.shared.v2.u32 [%0], {%1,%2};" ::"r"(addr), "r"(v.x), "r"(v.y) : "memory"); }
__device__ __forceinline__ void lds(uint32_t& v, uint32_t addr) { asm volatile("ld.shared.u32 %0, [%1];" : "=r"(v) : "r"(addr) : "memory"); }
__device__ __forceinline__ void lds(uint2& v, uint32_t addr) { asm volatile("ld.shared.v2.u32 {%0,%1}, [%2];" : "=r"(v.x), "=r"(v.y) : "r"(addr) : "memory"); }
__host__ __device__ constexpr uint32_t h2(uint32_t h) { return h | (h << 16); }
constexpr uint32_t H_2 = h2(0x4000), H_1_2 = h2(0x3800), H_1_4 = h2(0x3400), H_1_8 = h2(0x3000), H_1_16 = h2(0x2C00), H_1_32 = h2(0x2800),
                   H_N4 = h2(0xC400), H_N2 = h2(0xC000), H_N1_2 = h2(0xB800), H_N1_4 = h2(0xB400), H_N17_4 = h2(0xC440), H_1 = h2(0x3C00), H_N1 = h2(0xBC00);
__device__ __forceinline__ uint32_t hfma(uint32_t a, uint32_t b, uint32_t c) {
  uint32_t r; asm("fma.rn.f16x2 %0, %1, %2, %3;" : "=r"(r) : "r"(a), "r"(b), "r"(c)); return r;
}
__device__ __forceinline__ uint32_t hadd(uint32_t a, uint32_t b) { uint32_t r; asm("add.rn.f16x2 %0, %1, %2;" : "=r"(r) : "r"(a), "r"(b)); return r; }
__device__ __forceinline__ uint32_t hsub(uint32_t a, uint32_t b) { uint32_t r; asm("sub.rn.f16x2 %0, %1, %2;" : "=r"(r) : "r"(a), "r"(b)); return r; }
__device__ __forceinline__ uint2 hfma(uint2 a, uint32_t b, uint2 c) { return make_uint2(hfma(a.x, b, c.x), hfma(a.y, b, c.y)); }
__device__ __forceinline__ uint2 hadd(uint2 a, uint2 b) { return make_uint2(hadd(a.x, b.x), hadd(a.y, b.y)); }
__device__ __forceinline__ uint2 hsub(uint2 a, uint2 b) { return make_uint2(hsub(a.x, b.x), hsub(a.y, b.y)); }
__device__ __forceinline__ uint32_t bmul(uint32_t x, uint32_t k) { uint32_t z; asm("mul.rn.bf16x2 %0, %1, %2;" : "=r"(z) : "r"(x), "r"(k)); return z; }
__device__ __forceinline__ void scale(uint32_t& x, uint32_t k, uint32_t& m) { x = bmul(x, k); m |= x; }
__device__ __forceinline__ void scale(uint2& x, uint32_t k, uint32_t& m) {
  x.x = bmul(x.x, k); x.y = bmul(x.y, k);
  asm("lop3.b32 %0, %0, %1, %2, 0xFE;" : "+r"(m) : "r"(x.x), "r"(x.y));
}
__device__ __forceinline__ void tohalf(uint32_t& z) { z = (z & 0x7FFF7FFFu) * 7 + z; }
__device__ __forceinline__ void tohalf(uint2& z) { tohalf(z.x); tohalf(z.y); }
__device__ __forceinline__ bool out_of_range(uint32_t m) {
  m = __reduce_or_sync(0xffffffffu, m & 0x7FFF7FFFu);
  return (m & 0x78007800u) || (m && !(m & 0x06000600u));
}

template <typename V>
__device__ __forceinline__ void planes8(V (&d)[8], uint32_t dp, uint32_t dq, uint32_t dr, uint32_t ds) {
  const V ec = hfma(d[4], H_N17_4, hadd(d[6], d[2])), oc = hfma(d[3], H_N17_4, hadd(d[5], d[1]));
  sts(dr, hadd(ec, oc)); sts(dr + TWG, hsub(ec, oc));
#pragma unroll
  for (int k = 0; k < 6; k++) d[k] = hsub(d[k + 2], d[k]);
  const V ea = hfma(d[2], H_N4, d[4]), oa = hfma(d[1], H_N4, d[3]);
  sts(dp, hfma(oa, H_1_2, ea)); sts(dq, hfma(oa, H_N1_2, ea));
  sts(ds, hfma(hfma(d[0], H_N4, d[2]), H_N1_4, ea)); sts(ds + TWG, hfma(oa, H_N1_4, hfma(d[3], H_N4, d[5])));
  const V eb = hfma(d[2], H_N1_4, d[4]), ob = hfma(d[1], H_N1_4, d[3]);
  sts(dp + TWG, hfma(ob, H_2, eb)); sts(dq + TWG, hfma(ob, H_N2, eb));
}
template <typename V>
__device__ __forceinline__ void planes4(V (&d)[8], uint32_t dp, uint32_t dq) {
  sts(dp, hadd(d[2], d[1])); sts(dp + TWG, hsub(d[2], d[1]));
  sts(dq, hsub(d[2], d[0])); sts(dq + TWG, hsub(d[3], d[1]));
}

constexpr uint32_t BHI = 256 >> 4, BLO = (128 >> 4) << 16, AHI = 128 >> 4, ALO = (TCOL >> 4) << 16;
__device__ __forceinline__ uint64_t desc(uint32_t lo, uint32_t hi) { uint64_t d; asm("mov.b64 %0, {%1,%2};" : "=l"(d) : "r"(lo), "r"(hi)); return d; }

typedef uint32_t Acc[48];
struct Ctx {
  uint32_t sb;
  uint64_t ad, bd;
  uint32_t b0;
  uint32_t me, ra, tx;
  uint32_t ok;
  bool one;
  uint32_t wg, xs, xr;
  uint32_t w[12];
  uint32_t k, sg;
  const char* o;
  bool on, yes;
};
__device__ __forceinline__ void arrive(uint32_t bar, bool on) {
  asm volatile("{\n.reg .pred p;\nsetp.ne.b32 p, %1, 0;\n@p mbarrier.arrive.shared::cta.b64 _, [%0];\n}" ::"r"(bar), "r"((uint32_t)on) : "memory");
}
template <int S>
__device__ __forceinline__ void release(Ctx& C, uint32_t me, uint32_t tx) {
  asm volatile(
      "{\n.reg .pred p;\n"
      "setp.ne.b32 p, %1, 0;\n"
      "@p mbarrier.arrive.expect_tx.shared::cta.b64 _, [%0], %1;\n}" ::"r"(C.b0 + 16 * S), "r"(tx) : "memory");
  asm volatile(
      "{\n.reg .pred p;\n"
      "setp.eq.b32 p, %0, %2;\n"
      "@p mbarrier.arrive.shared::cluster.b64 _, [%1];\n}" ::"r"(me), "r"(C.ra), "n"(16 * S) : "memory");
}
template <int SYNC, int ID0, int ID1>
__device__ __forceinline__ void bar(uint32_t wg) {
  if (SYNC) asm volatile("{\n.reg .pred p;\nsetp.ne.b32 p, %0, 0;\n@!p bar.sync %1, 256;\n@p bar.sync %2, 256;\n}" ::"r"(wg), "n"(ID0), "n"(ID1) : "memory");
  else asm volatile("{\n.reg .pred p;\nsetp.ne.b32 p, %0, 0;\n@!p bar.arrive %1, 256;\n@p bar.arrive %2, 256;\n}" ::"r"(wg), "n"(ID0), "n"(ID1) : "memory");
}
__device__ __forceinline__ void sent(Ctx& C) { bar<0, 1, 2>(C.wg); }
__device__ __forceinline__ void await_sent(Ctx& C) { bar<1, 2, 1>(C.wg); }
__device__ __forceinline__ void sent2(Ctx& C) { bar<0, 10, 11>(C.wg); }
__device__ __forceinline__ void await_sent2(Ctx& C) { bar<1, 11, 10>(C.wg); }
__device__ __forceinline__ void await_taken(Ctx& C) { bar<1, 3, 4>(C.wg); }
__device__ __forceinline__ void taken(Ctx& C, uint32_t x) { if ((x & blockIdx.y) == 0) bar<0, 4, 3>(C.wg); }

__host__ __device__ constexpr int xoff(int u, int h) { return u * TUNIT + h * 2048; }
template <int B, int OF>
__device__ __forceinline__ void send(const Acc& A, uint32_t addr) {
  asm volatile("st.shared.v4.u32 [%4 + %5], {%0,%1,%2,%3};" ::"r"(A[4 * B]), "r"(A[4 * B + 1]), "r"(A[4 * B + 2]), "r"(A[4 * B + 3]), "r"(addr), "n"(OF) : "memory");
}
template <int B, int OF>
__device__ __forceinline__ void recv(Acc& A, uint32_t addr, bool on) {
  asm volatile("{\n.reg .pred p;\nsetp.ne.b32 p, %6, 0;\n@p ld.shared.v4.u32 {%0,%1,%2,%3}, [%4 + %5];\n}"
               : "+r"(A[4 * B]), "+r"(A[4 * B + 1]), "+r"(A[4 * B + 2]), "+r"(A[4 * B + 3]) : "r"(addr), "n"(OF), "r"((uint32_t)on) : "memory");
}
template <int OF>
__device__ __forceinline__ void fetch4(uint32_t* w, uint32_t addr) {
  asm volatile("ld.shared.v4.u32 {%0,%1,%2,%3}, [%4 + %5];" : "=r"(w[0]), "=r"(w[1]), "=r"(w[2]), "=r"(w[3]) : "r"(addr), "n"(OF) : "memory");
}
template <int I, int N>
__device__ __forceinline__ void add_to(Acc& A, const uint32_t* w, uint32_t sg) {
#pragma unroll
  for (int j = 0; j < N; j++) asm volatile("fma.rn.f16x2 %0, %1, %2, %0;" : "+r"(A[I + j]) : "r"(w[j]), "r"(sg));
}
template <int I, int N>
__device__ __forceinline__ void join(Acc& A, const Acc& B) {
#pragma unroll
  for (int j = I; j < I + N; j++) asm volatile("add.rn.f16x2 %0, %0, %1;" : "+r"(A[j]) : "r"(B[j]));
}
template <int B, int OF>
__device__ __forceinline__ void split(Acc& A, const Acc& Bb, uint32_t* w, uint32_t addr) {
#pragma unroll
  for (int j = 0; j < 4; j++)
    asm volatile("sub.rn.f16x2 %0, %1, %2;\nadd.rn.f16x2 %1, %1, %2;" : "=&r"(w[j]), "+r"(A[4 * B + j]) : "r"(Bb[4 * B + j]));
  asm volatile("st.shared.v4.u32 [%4 + %5], {%0,%1,%2,%3};" ::"r"(w[0]), "r"(w[1]), "r"(w[2]), "r"(w[3]), "r"(addr), "n"(OF) : "memory");
}
__host__ __device__ constexpr int pj(int k) { return 2 * (k >> 2) + (k & 1); }
__host__ __device__ constexpr int pp(int k) { return (k >> 1) & 1; }
template <int K>
__device__ __forceinline__ void rows(const Acc& P, Acc& Q, Acc& R, uint32_t* w) {
#pragma unroll
  for (int i = 0; i < 4; i++) {
    const int j = 8 * pj(K) + 2 * i + pp(K);
    asm volatile(
        "{\n.reg .b32 a, b;\n"
        "fma.rn.f16x2 a, %1, %4, %2;\n fma.rn.f16x2 b, %1, %5, %2;\n fma.rn.f16x2 %1, %1, %6, %2;\n"
        "fma.rn.f16x2 %0, %3, %7, a;\n fma.rn.f16x2 %2, %3, %8, b;\n add.rn.f16x2 %1, %1, %3;\n}"
        : "=r"(w[i]), "+r"(Q[j]), "+r"(R[j]) : "r"(P[j]), "r"(H_1_8), "r"(H_1_2), "r"(H_1_32), "r"(H_1_4), "r"(H_1_16));
  }
}
__device__ __forceinline__ uint32_t tobf(uint32_t h, uint32_t k) {
  uint32_t o;
  asm volatile("{\n.reg .b16 l, u;\n.reg .f32 a, b;\n.reg .b32 t;\nmov.b32 {l, u}, %1;\ncvt.f32.f16 a, l;\ncvt.f32.f16 b, u;\n"
               "cvt.rn.bf16x2.f32 t, b, a;\nmul.rn.bf16x2 %0, t, %2;\n}" : "=r"(o) : "r"(h), "r"(k));
  return o;
}
template <int K>
__device__ __forceinline__ void stg4(const char* o, const uint32_t* r) {
  asm volatile("st.global.cs.v4.u32 [%4 + %5], {%0,%1,%2,%3};" ::"r"(r[0]), "r"(r[1]), "r"(r[2]), "r"(r[3]), "l"(o), "n"(pp(K) * 8 * CH * 2 + pj(K) * 64) : "memory");
}
template <int K, int LAST = 0>
__device__ __forceinline__ void put(const Acc& A, Ctx& C) {
  uint32_t* w = C.w + (LAST ? 4 * (K & 1) : 8);
#pragma unroll
  for (int i = 0; i < 4; i++) w[i] = tobf(A[8 * pj(K) + 2 * i + pp(K)], C.k);
  stg4<K>(C.o, w);
}

constexpr uint64_t OUT_R = 0x555491110ull, OUT_S = 0x084210842108421ull, OUT_M = 0x151551540ull, OUT_F = 0x281015555ull;
constexpr int E0_AT = 6, E1_AT = 27;
__host__ __device__ constexpr int below(uint64_t m, int n) { return __builtin_popcountll(m & ((1ull << n) - 1)); }
static_assert(below(OUT_R, 36) == 12 && below(OUT_S, 60) == 12 && below(OUT_M, 35) == 12 && below(OUT_F, 36) == 12, "pieces");
static_assert(!(OUT_R & 15) && !(OUT_M & 0xC03F) && !(OUT_M & (OUT_M << 1)) && below(OUT_M, 8) <= 1 && below(OUT_M, 12) <= 4 && below(OUT_M, 24) <= 8 && below(OUT_M, 28) <= 9 && !(OUT_F & 0x7E000000) && E0_AT >= 6 && E1_AT >= 27, "order");

__host__ __device__ constexpr int r_out(int n) { return n >= 96 && n < 100 ? n - 96 : n == 124 || n == 125 ? n - 120 : -1; }
__host__ __device__ constexpr int d_out(int n) { return n >= 108 && n < 112 ? n - 108 : n == 122 || n == 123 ? n - 118 : -1; }
__host__ __device__ constexpr int r_in(int n) { return n >= 101 && n < 109 ? n - 101 : n == 130 || n == 131 ? n - 122 : n == 134 || n == 135 ? n - 124 : -1; }
__host__ __device__ constexpr int d_in(int n) { return n >= 112 && n < 120 ? n - 112 : n == 128 || n == 129 ? n - 120 : n == 132 || n == 133 ? n - 122 : -1; }
constexpr uint32_t XU_R = 0x750354, XU_D = 0x425421, XU_F = 0x984210;
template <int N, int FILL>
__device__ __forceinline__ void early(Acc& P, Acc& Q, Acc& R, Acc& S, Ctx& C) {
  if constexpr (FILL) {
    constexpr int I = N - 61;
    if constexpr (I == 0) await_sent(C);
    if constexpr (I >= 0 && I < 6) { fetch4<xoff(unit(XU_F, I), 0)>(C.w, C.xr); fetch4<xoff(unit(XU_F, I), 1)>(C.w + 4, C.xr); }
  } else {
    if constexpr (N == 101 || N == 116) await_sent(C);
    if constexpr (N == 112 || N == 128) await_sent2(C);
    if constexpr (r_in(N) >= 0) {
      constexpr int B = r_in(N);
      fetch4<xoff(unit(XU_R, B / 2), B & 1)>(C.w + 4, C.xr);
    }
    if constexpr (d_in(N) >= 0) recv<d_in(N), xoff(unit(XU_D, d_in(N) / 2), d_in(N) & 1)>(Q, C.xr, C.yes);
  }
}
template <int N, int FILL>
__device__ __forceinline__ void side(Acc& P, Acc& Q, Acc& R, Acc& S, Ctx& C) {
  const uint32_t te = C.sb + BAR_TEMPTY;
  if constexpr (FILL) {
    constexpr int I = N - 36, X = N - 54;
    if constexpr ((OUT_F >> I) & 1) { if (C.on) put<below(OUT_F, I)>(S, C); }
    if constexpr (X >= 0 && X < 6) { send<2 * X, xoff(unit(XU_F, X), 0)>(P, C.xs); send<2 * X + 1, xoff(unit(XU_F, X), 1)>(P, C.xs); }
    if constexpr (X == 5) sent(C);
    if constexpr (N == 66) { if (C.wg) asm volatile("bar.sync 6, 256;" ::: "memory"); }
    if constexpr (N == 71) { if (!C.wg) asm volatile("bar.arrive 6, 256;" ::: "memory"); }
    if constexpr (N >= 61 && N < 67) { if (C.yes) add_to<8 * (N - 61), 8>(P, C.w, C.sg); }
  } else if constexpr (N < 36) {
    if constexpr (N == 0) arrive(te + 16, C.one);
    if constexpr (N < 4) { if (C.on) join<12 * N, 12>(S, Q); }
    if constexpr ((OUT_R >> N) & 1) { if (C.on) put<below(OUT_R, N)>(R, C); }
    if constexpr (N == 30) arrive(te + 24, C.one);
  } else if constexpr (N < 96) {
    if constexpr ((OUT_S >> (N - 36)) & 1) { if (C.on) put<below(OUT_S, N - 36)>(S, C); }
    if constexpr (N == 48) arrive(te + 32, C.one);
    if constexpr (N == 72) arrive(te + 40, C.one);
  } else {
    constexpr int I = N - 108;
    if constexpr (I > 0) {
      if constexpr ((OUT_M >> (I - 1)) & 1) {
        if (C.yes) {
#pragma unroll
          for (int i = 0; i < 4; i++) C.w[8 + i] = tobf(C.w[i], C.k);
        }
        stg4<below(OUT_M, I - 1)>(C.o, C.w + 8);
      }
    }
    if constexpr (I >= 0) {
      if constexpr ((OUT_M >> I) & 1) { if (C.yes) rows<below(OUT_M, I)>(P, Q, R, C.w); }
    }
    if constexpr (N == 110 || N == 122) await_taken(C);
    if constexpr (r_out(N) >= 0) {
      constexpr int X = r_out(N);
      send<2 * X, xoff(unit(XU_R, X), 0)>(R, C.xs); send<2 * X + 1, xoff(unit(XU_R, X), 1)>(R, C.xs);
    }
    if constexpr (r_in(N) >= 0) {
      if (C.yes) {
        add_to<4 * r_in(N), 4>(R, C.w + 4, C.sg);
      }
    }
    if constexpr (d_out(N) >= 0) {
      constexpr int X = d_out(N);
      if (C.yes) { split<2 * X, xoff(unit(XU_D, X), 0)>(P, Q, C.w + 4, C.xs); split<2 * X + 1, xoff(unit(XU_D, X), 1)>(P, Q, C.w, C.xs); }
    }
    if constexpr (N == 99 || N == 111) sent(C);
    if constexpr (N == 109 || N == 125) sent2(C);
    if constexpr (N == 108) taken(C, R[31]);
    if constexpr (N == 120) taken(C, Q[11] | Q[15] | Q[19] | Q[23] | Q[27] | Q[31]);
    if constexpr (I == E0_AT) arrive(te, C.one && ((Q[3] | Q[7]) & blockIdx.y) == 0);
    if constexpr (I == E1_AT) arrive(te + 8, C.one && ((R[47] | Q[35] | Q[39] | Q[43] | Q[47]) & blockIdx.y) == 0);
  }
}
template <int W, int LEAD, int N0, int FILL, int J = 0>
__device__ __forceinline__ void group(Acc& P, Acc& Q, Acc& R, Acc& S, Ctx& C, uint64_t a) {
  constexpr int N = N0 + J;
  if (!C.ok) mbar_wait(C.b0 + 16 * (N % NUST), (N / NUST) & 1);
  wg_fence();
  wgmma192<LEAD && J == 0>(W == 0 ? P : W == 1 ? Q : W == 2 ? R : S, a + (((J / 3) * 2 * TCOL + (J % 3) * 16) >> 4), C.bd + (N % NUST) * (UTILE >> 4), blockIdx.y);
  wg_commit();
  C.ok = mbar_try(C.b0 + 16 * ((N + 1) % NUST), ((N + 1) / NUST) & 1);
  early<N, FILL>(P, Q, R, S, C);
  wg_wait<1>();
  if constexpr (!FILL || N + NUST <= 72) release<(N + NUST - 1) % NUST>(C, N || C.on ? C.me : 0, N || C.on ? C.tx : 0);
  side<N, FILL>(P, Q, R, S, C);
  if constexpr (J < 5) group<W, LEAD, N0, FILL, J + 1>(P, Q, R, S, C, a);
}

__device__ __forceinline__ void fetch(const CUtensorMap* map, uint32_t bytes, uint32_t dst, uint32_t bar, int c, int x, int y, uint64_t pol) {
  asm volatile("{\n.reg .pred p;\nelect.sync _|p, 0xffffffff;\n"
               "@p mbarrier.arrive.expect_tx.shared::cta.b64 _, [%2], %6;\n"
               "@p cp.async.bulk.tensor.3d.shared::cluster.global.mbarrier::complete_tx::bytes.L2::cache_hint [%0], [%1, {%3,%4,%5}], [%2], %7;\n}"
               ::"r"(dst), "l"(map), "r"(bar), "r"(c), "r"(x), "r"(y), "r"(bytes), "l"(pol) : "memory");
}
constexpr uint64_t POL_FIRST = 0x12F0000000000000ull, POL_SAME = 0x10F0000000000000ull;

struct Params { uint8_t* U; uint32_t* ready; int lg, mlg, ufirst, ustep, nunit, umax, nfill, s0, second, nfirst, nall; uint4 un[12]; };

__global__ void __launch_bounds__(NTHREADS, 1) wino_main(const __grid_constant__ CUtensorMap xmap8, const __grid_constant__ CUtensorMap xmap4,
                                                         const __grid_constant__ CUtensorMap xmap1, const __grid_constant__ CUtensorMap xmap0,
                                                         const __nv_bfloat16* __restrict__ xin, const __nv_bfloat16* __restrict__ wgt,
                                                         __nv_bfloat16* __restrict__ out, const Params P) {
  extern __shared__ __align__(1024) uint8_t smem[];
  { const uint32_t l = threadIdx.x * gridDim.x + blockIdx.x; if (l < 9 * CH * CH * 2 / 128) asm volatile("prefetch.global.L2 [%0];" ::"l"((const char*)wgt + l * 128u)); }
  const uint32_t sb = smem_u32(smem);
  const int warp = __shfl_sync(0xffffffffu, threadIdx.x >> 5, 0), lane = threadIdx.x & 31;
  const uint32_t cm = (1u << P.lg) - 1, rank = blockIdx.x & cm, mm = (1u << P.mlg) - 1, mrank = blockIdx.x & mm;
  const int cl = blockIdx.x >> P.lg;
  const int nit = min(P.umax, (P.nunit - cl * P.ufirst + P.ustep - 1) / P.ustep), fu = cl % P.nfill;
  auto first = [&](int i) {
    const int u = cl * P.ufirst + i * P.ustep, q = (u * (205 << (P.lg - 1))) >> 12;
    const int st = P.s0 + (i < nit ? q : fu >> (3 - P.lg));
    const int y = i < nit ? ((u - q * (40 >> P.lg)) * 6 << P.lg) + 6 * rank : 240 + ((fu & ((8 >> P.lg) - 1)) * 2 << P.lg) + 2 * rank;
    return (st & 7) * 64 + ((st >> 3) * 256 + y) * IMG;
  };

  auto origin = [&](int i) { int o; asm volatile("ld.shared.u32 %0, [%1];" : "=r"(o) : "r"(sb + SM_ORG + 4 * i)); return o; };
  if (warp == 11 && lane < 7) sts(sb + SM_ORG + 4 * lane, (uint32_t)first(min(lane, nit)));

  if (warp != 11) asm volatile("barrier.cluster.arrive.relaxed.aligned;" ::: "memory");
  if (warp == 10) {
    sts(sb + SM_EXP, min(sample_exp((const char*)wgt + lane * (4 * 5168), 5168), 240u));
    asm volatile("bar.arrive 11, 288;" ::: "memory");
  }
  if (warp == 9) {
    const uint32_t e = sample_exp((const char*)xin + ((uint32_t)(first(0) + 2 * lane + (lane & 1) * IMG) * (CH * 2u) + lane % 6 * 64), CH / 2 + 16);
    sts(sb + SM_EXP + 4, e ? min(e, 138u) : 120);
    asm volatile("bar.arrive 12, 192;\nbar.arrive 13, 288;" ::: "memory");
  }
  if (warp < 8) {
    const int t0 = warp * gridDim.x + blockIdx.x;
    if (P.second || t0 >= NFILT) { cluster_wait(); asm volatile("bar.sync 11, 288;" ::: "memory"); }
    if (!P.second) {
      bool ok = true;
      if (t0 >= NFILT) made(P.ready, 1);
#pragma unroll 1
      for (int t = t0; t < NFILT; t += 8 * gridDim.x) ok = filter_task(wgt, P.U, t, lane, sb + SM_EXP, t == t0, t + 8 * gridDim.x >= NFILT, P.ready) && ok;
      if (!ok) atomicOr(P.ready, 1u << 31);
      made(P.ready, 1024);
    }
  }
  if (warp == 8) {
    uint32_t v; asm volatile("ld.volatile.global.u32 %0, [%1];" : "=r"(v) : "l"(P.ready) : "memory");
    if (v < P.nfirst) __nanosleep(100);
  }
  if (threadIdx.x == 352) {
    for (int i = 0; i < 2 * NUST; i++) { mbar_init(sb + BAR_U + 16 * i, 1); mbar_init(sb + BAR_U + 16 * i + 8, mm + 1); }
    for (int i = 0; i < 6; i++) { mbar_init(sb + BAR_TFULL + 8 * i, 5); mbar_init(sb + BAR_TEMPTY + 8 * i, 8); }
    sts(sb + SM_FLAG, 0u);
    asm volatile("fence.mbarrier_init.release.cluster;" ::: "memory");
    for (int i = 0; i < 2 * NUST; i++) mbar_expect_tx(sb + BAR_U + 16 * i, UTILE);
  }
  const uint32_t rbar = __shfl_sync(0xffffffffu, sb + BAR_RFULL + (warp & 3) * 16, 0), rbuf = sb + SM_R + (warp & 3) * (2 * RSLOT);
  if (warp >= 12) {
    if (lane == 0) {
      mbar_init(rbar, 1); mbar_init(rbar + 8, 1);
      asm volatile("fence.mbarrier_init.release.cluster;" ::: "memory");
    }
    __syncwarp();
    if (!P.second) __nanosleep(300);
    const int o = first(0);
#pragma unroll
    for (int i = 0; i < 2; i++)
      fetch(nit ? &xmap0 : &xmap4, nit ? RSLOT : RSLOT / 2, rbuf + i * RSLOT, rbar + 8 * i, 0, (o & 511) - 1 + (warp & 3) * 16 + i * 4, (o >> 9) - 1, POL_SAME);
  }
  __syncwarp();
  if (warp == 11) asm volatile("barrier.cluster.arrive.relaxed.aligned;" ::: "memory");
  if (warp == 8 || warp > 10) cluster_wait();
  if (warp > 10) asm volatile("bar.sync 12, 192;" ::: "memory");
  if (warp < 8) asm volatile("bar.sync 13, 288;" ::: "memory");
  uint2 ex;
  lds(ex, sb + SM_EXP);
  const uint32_t kin = h2((139 - ex.y) << 7);

  if (warp >= 12) {
    asm volatile("setmaxnreg.dec.sync.aligned.u32 40;");
    const int wi = warp - 12;
    const uint32_t tb = __shfl_sync(0xffffffffu, sb + SM_T + ((lane >> 1) & 3) * TCOL + (wi * 16 + (lane >> 3)) * 16 + (lane & 1) * 8, lane);
    const uint32_t src = rbuf + __shfl_sync(0xffffffffu, lane * 8, lane);
    const uint32_t nb = __shfl_sync(0xffffffffu, lane & blockIdx.y, lane);
    int o = origin(0), x = (o & 511) - 1 + wi * 16, y = (o >> 9) - 1;
    uint32_t m = 0;
    auto chunk = [&](auto fill, int i, uint32_t c, int xn, int yn) {
      constexpr int NR = fill.value ? 4 : 8;
      const CUtensorMap* const map = fill.value ? &xmap4 : &xmap8;
      const uint4 un = P.un[6 * fill.value + c];
      const bool turn = c == 5, half = fill.value || (turn && i + 1 == nit);
      const CUtensorMap* const map1 = half ? &xmap4 : &xmap8;
      const int c1 = turn ? 0 : c * 32 + 32, x1 = turn ? xn : x, y1 = turn ? yn : y;
      const uint32_t n1 = half ? RSLOT / 2 : RSLOT;
#pragma unroll
      for (int q = 0; q < 4; q++) {
        const uint32_t sl = (q & 1) * RSLOT, rb = rbar + (q & 1) * 8;
        uint2 d[8];
        mbar_wait_sleep(rb, q >> 1);
#pragma unroll
        for (int r = 0; r < NR; r++) lds(d[r], src + sl + r * RROW);
#pragma unroll
        for (int r = 0; r < NR; r++) scale(d[r], kin, m);
        if (q < 2) fetch(!fill.value && i + c == 0 ? &xmap0 : map, NR * RROW | (m & nb), rbuf + sl, rb, c * 32, x + 8 + 4 * q, y, c & 1 ? POL_FIRST : POL_SAME);
        else if (!fill.value || !turn) fetch(map1, n1 | (m & nb), rbuf + sl, rb, c1, x1 + 4 * q - 8, y1, c & 1 ? POL_SAME : POL_FIRST);
#pragma unroll
        for (int r = 0; r < NR; r++) tohalf(d[r]);
        if (q == 0 && (!fill.value || c < 3)) mbar_wait_sleep(sb + BAR_TEMPTY + 8 * c, (i & 1) ^ (c < 2));
        if (q == 0 && wi == 0) TRACE(2, tn);
        const uint32_t t = tb + 64 * q;
        if (fill.value) planes4(d, t + un.x, t + un.y);
        else planes8(d, t + un.x, t + un.y, t + un.z, t + un.w);
      }
      if (turn) {
        if (out_of_range(m)) asm volatile("red.shared.or.b32 [%0], %1;" ::"r"(sb + SM_FLAG), "r"(1u << i) : "memory");
        m = 0; x = xn; y = yn;
      }
      asm volatile("fence.proxy.async.shared::cta;" ::: "memory");
      __syncwarp();
      arrive_elect(sb + BAR_TFULL + 8 * c);
    };
#pragma unroll 1
    for (int i = 0; i < nit; i++) {
      o = origin(i + 1);
#pragma unroll 1
      for (uint32_t c = 0; c < 6; c++) chunk(std::false_type(), i, c, (o & 511) - 1 + wi * 16, (o >> 9) - 1);
    }
#pragma unroll 1
    for (uint32_t c = 0; c < 6; c++) chunk(std::true_type(), nit, c, 0, 0);
    cluster_sync();
  } else if (warp >= 8) {
    asm volatile("setmaxnreg.dec.sync.aligned.u32 24;");
    if (warp < 10) {
      const uint32_t g = warp - 8, s0 = mrank ^ (13 * g & mm);
      const uint32_t ring = sb + SM_U + g * (NUST * UTILE), ub = sb + BAR_U + g * (NUST * 16);
      if (warp == 8) {
        uint32_t v, i = 0;
        do { asm volatile("ld.acquire.gpu.global.u32 %0, [%1];" : "=r"(v) : "l"(P.ready) : "memory"); if (++i > 5000000u) __trap(); } while ((v & 1023) < P.nfirst);
        asm volatile("bar.arrive 7, 64;" ::: "memory");
      }
      asm volatile("bar.sync 9, 64;" ::: "memory");
      asm volatile("fence.proxy.async.global;" ::: "memory");
      uint32_t ph = 1;
#pragma unroll 1
      for (int i = 0; i <= nit; i++) {
        const uint8_t* from = P.U + g * UWG + (i < nit ? 0 : NROUND * NUST * UTILE);
#pragma unroll 1
        for (uint32_t t = 0; t < (i < nit ? NROUND : NFROUND); t++, ph ^= 1, from += NUST * UTILE) {
          if (i == 0 && t == 36 / NUST) asm volatile("bar.sync 8, 96;\nfence.proxy.async.global;" ::: "memory");
#pragma unroll 1
          for (uint32_t s = s0; mm == 15 ? s < 9 : s < 8 || (s < 16 && s0 == (4 & mm)); s = s + mm + 1 < 8 ? s + mm + 1 : s < 8 && mm < 15 ? 8 : 16) {
            mbar_wait(ub + 16 * s + 8, ph);
            asm volatile(
                "{\n.reg .pred p;\n"
                "elect.sync _|p, 0xffffffff;\n"
                "@p cp.async.bulk.shared::cluster.global.mbarrier::complete_tx::bytes.multicast::cluster [%0], [%1], %2, [%4], %3;\n}"
                ::"r"(ring + s * UTILE), "l"(from + s * UTILE), "n"(UTILE), "h"((uint16_t)((2u << mm) - 1)), "r"(ub + 16 * s) : "memory");
          }
        }
      }
    } else if (warp == 10) {
      uint32_t v, i = 0;
      do { asm volatile("ld.acquire.gpu.global.u32 %0, [%1];" : "=r"(v) : "l"(P.ready) : "memory"); if (++i > 5000000u) __trap(); } while (((v >> 10) & 1023) < P.nfirst);
      if (v >> 31) asm volatile("red.shared.or.b32 [%0], %1;" ::"r"(sb + SM_FLAG), "r"(0xFFFFu) : "memory");
      __syncwarp();
      asm volatile("bar.arrive 8, 96;" ::: "memory");
      asm volatile("bar.sync 7, 64;" ::: "memory");
      if (lane == 0 && atomicAdd(P.ready + 32, 1) == P.nall - 1) P.ready[0] = P.ready[32] = 0;
      __syncwarp();
      asm volatile("griddepcontrol.launch_dependents;");
      auto ahead = [&](int i, uint32_t sl, int r) {
        const int o = origin(i), nr = i < nit ? 6 : 2;
        auto row = [&](int y) {
          asm volatile("{\n.reg .pred p;\nelect.sync _|p, 0xffffffff;\n@p cp.async.bulk.prefetch.tensor.3d.L2.global [%0, {%1,%2,%3}];\n}"
                       ::"l"(&xmap1), "r"(sl * 64), "r"((o & 511) - 1), "r"((o >> 9) + y) : "memory");
        };
        if (r < nr) row(r);
        if (r == 0 && rank == 0) row(-1);
        if (r + 1 == nr && rank == cm) row(nr);
      };
      uint32_t ph = 0;
#pragma unroll 1
      for (int i = 0; i <= nit; i++) {
#pragma unroll 1
        for (uint32_t t = 0; t < (i < nit ? NROUND : NFROUND - 3); t++, ph ^= 1) {
#pragma unroll 1
          for (int n = P.second ? 400 : 20; n && !mbar_try(sb + BAR_U + 16 * rank, ph); n--) __nanosleep(100);
          if (t - 1 < 6) ahead(i, 2, t - 1);
          if (i < nit && t - 6 < 6) ahead(i + 1, 0, t - 6);
          if (i < nit && t - 10 < 6) ahead(i + 1, 1, t - 10);
          if (((cl + t) & 7) == 0 && !P.second) {
            const uint32_t r = i == nit ? NROUND + t + 3 : t + 3 < NROUND || i + 1 == nit ? t + 3 : t + 3 - NROUND;
            if (lane < (rank == 4 ? 4 : 2))
              asm volatile("cp.async.bulk.prefetch.L2.global [%0], %1;" ::"l"(P.U + ((lane & 1) * UWG + (r * NUST + (lane >> 1 ? 8 : rank)) * UTILE)), "n"(UTILE) : "memory");
            __syncwarp();
          }
        }
      }
    } else {
      const uint32_t tb = sb + SM_T + ((lane >> 2) & 3) * TCOL + (64 + (lane >> 4)) * 16 + (lane & 3) * 4;
      uint32_t iph = 0;
#pragma unroll 1
      for (int i = 0; i <= nit; i++, iph ^= 1) {
        const int o = origin(i), x = (o & 511) + 63 + (lane >> 4), y = (o >> 9) - 1, nr = i < nit ? 8 : 4;
        const char* p = (const char*)xin + (uint32_t)(o + 63 + (lane >> 4)) * (CH * 2u) + (lane & 15) * 4;
        uint32_t m = 0;
#pragma unroll 1
        for (uint32_t c = 0; c < 6; c++, p += 64) {
          uint32_t d[8];
#pragma unroll
          for (int r = 0; r < 8; r++) {
            d[r] = 0;
            if (x < IMG && (uint32_t)(y + r) < IMG && r < nr) asm volatile("ld.global.nc.u32 %0, [%1];" : "=r"(d[r]) : "l"(p + (r - 1) * ROWB));
          }
#pragma unroll
          for (int r = 0; r < 8; r++) { scale(d[r], kin, m); tohalf(d[r]); }
          if (i < nit || c < 3) mbar_wait_sleep(sb + BAR_TEMPTY + 8 * c, iph ^ (c < 2));
          const uint4 un = P.un[i < nit ? c : 6 + c];
          if (i < nit) planes8(d, tb + un.x, tb + un.y, tb + un.z, tb + un.w);
          else planes4(d, tb + un.x, tb + un.y);
          if (c == 5 && (m & 0x78007800u)) asm volatile("red.shared.or.b32 [%0], %1;" ::"r"(sb + SM_FLAG), "r"(1u << i) : "memory");
          asm volatile("fence.proxy.async.shared::cta;" ::: "memory");
          __syncwarp();
          arrive_elect(sb + BAR_TFULL + 8 * c);
        }
      }
      if (P.second == 2) asm volatile("griddepcontrol.wait;" ::: "memory");
    }
    __syncwarp();
    cluster_sync();
  } else {
    const uint32_t ek = ex.x ? ex.x + ex.y - 119 : 0;
    asm volatile("setmaxnreg.inc.sync.aligned.u32 224;");
    const int wg = warp >> 2;
    Ctx C;
    C.sb = sb; C.wg = wg;
    C.b0 = sb + BAR_U + wg * (NUST * 16);
    C.bd = desc(BLO + (((sb + SM_U + wg * (NUST * UTILE)) & 0x3FFFF) >> 4), BHI);
    C.ad = desc(ALO + (((sb + SM_T + wg * TWG) & 0x3FFFF) >> 4), AHI);
    C.tx = __shfl_sync(0xffffffffu, (threadIdx.x & 127) == 0 ? UTILE : 0, lane);
    asm volatile("mapa.shared::cluster.u32 %0, %1, %2;" : "=r"(C.ra) : "r"(C.b0 + 16 * lane + 8), "r"(((lane == 8 && mm < 15 ? 4 : lane) ^ 13 * wg) & mm));
    C.ok = 0;
    const uint32_t t16 = __shfl_sync(0xffffffffu, (warp & 3) * 512 + lane * 16, lane);
    C.me = t16; C.one = (t16 & 511) == 0;
    C.xs = sb + SM_T + wg * TWG + t16;
    C.xr = sb + SM_T + (wg ^ 1) * TWG + t16;
    C.k = h2(ek << 7); C.sg = wg ? H_1 : H_N1;
    C.yes = C.sb != gridDim.x;
    const int drow = wg ? -2 * ROWB : 2 * ROWB;
    const char* const ob = (const char*)out + (uint32_t)(((warp & 3) * 16 + (lane >> 2)) * CH + (lane & 3) * 8) * 2u;
    C.o = ob;
#pragma unroll
    for (int i = 0; i < 12; i++) C.w[i] = 0;

    Acc A0, A1, A2, A3;
#pragma unroll
    for (int j = 0; j < 48; j++) { A0[j] = 0; A1[j] = 0; A2[j] = 0; A3[j] = 0; }
#define G(W, LEAD, N0, FILL, U) group<W, LEAD, N0, FILL>(A0, A1, A2, A3, C, C.ad + (U) * (TUNIT >> 4))
    uint32_t ph = 0;
#pragma unroll 1
    for (int item = 0;; item++) {
      C.on = item != 0;
      if (P.second && item == 2) {
        const int wait = (5 - nit) * 28000 - 16000;
        uint32_t c0, c;
        asm volatile("mov.u32 %0, %%clock;" : "=r"(c0));
        do { __nanosleep(500); asm volatile("mov.u32 %0, %%clock;" : "=r"(c)); } while ((int)(c - c0) < wait);
      }
      C.ad += item & blockIdx.y; C.bd += item & blockIdx.y;
      mbar_wait(sb + BAR_TFULL, ph);
      G(0, 1, 0, 0, unit(UN_P, 0));
      G(1, 1, 6, 0, unit(UN_Q, 0));
      mbar_wait(sb + BAR_TFULL + 8, ph);
      G(0, 0, 12, 0, unit(UN_P, 1)); G(1, 0, 18, 0, unit(UN_Q, 1));
      mbar_wait(sb + BAR_TFULL + 16, ph);
      G(0, 0, 24, 0, unit(UN_P, 2)); G(1, 0, 30, 0, unit(UN_Q, 2));
      C.o -= 2 * drow;
      if (item == nit) break;
      G(2, 1, 36, 0, unit(UN_R, 0)); G(2, 0, 42, 0, unit(UN_R, 1)); G(2, 0, 48, 0, unit(UN_R, 2));
      mbar_wait(sb + BAR_TFULL + 24, ph);
      G(2, 0, 54, 0, unit(UN_R, 3)); G(0, 0, 60, 0, unit(UN_P, 3)); G(1, 0, 66, 0, unit(UN_Q, 3));
      mbar_wait(sb + BAR_TFULL + 32, ph);
      G(2, 0, 72, 0, unit(UN_R, 4)); G(0, 0, 78, 0, unit(UN_P, 4)); G(1, 0, 84, 0, unit(UN_Q, 4));
      mbar_wait(sb + BAR_TFULL + 40, ph);
      G(2, 0, 90, 0, unit(UN_R, 5)); G(0, 0, 96, 0, unit(UN_P, 5)); G(1, 0, 102, 0, unit(UN_Q, 5));
      ph ^= 1;
      C.o = ob + (uint32_t)(origin(item) + (2 + wg) * IMG) * (CH * 2u);
      G(3, 1, 108, 0, unit(UN_S, 0)); G(3, 0, 114, 0, unit(UN_S, 1)); G(3, 0, 120, 0, unit(UN_S, 2));
      G(3, 0, 126, 0, unit(UN_S, 3)); G(3, 0, 132, 0, unit(UN_S, 4)); G(3, 0, 138, 0, unit(UN_S, 5));
      C.o += drow;
    }
    mbar_wait(sb + BAR_TFULL + 24, ph);
    G(0, 0, 36, 1, unit(UN_FP, 3));
    mbar_wait(sb + BAR_TFULL + 32, ph);
    G(0, 0, 42, 1, unit(UN_FP, 4));
    mbar_wait(sb + BAR_TFULL + 40, ph);
    G(0, 0, 48, 1, unit(UN_FP, 5));
    G(1, 0, 54, 1, unit(UN_FQ, 3)); G(1, 0, 60, 1, unit(UN_FQ, 4)); G(1, 0, 66, 1, unit(UN_FQ, 5));
#undef G
    wg_wait<0>();
    asm volatile("barrier.cluster.arrive.relaxed.aligned;" ::: "memory");
    uint32_t redo;
    asm volatile("ld.shared.u32 %0, [%1];" : "=r"(redo) : "r"(sb + SM_FLAG) : "memory");
    if (cl < P.nfill) {
      C.o = ob + (uint32_t)(origin(nit) + wg * IMG) * (CH * 2u);
      join<0, 48>(A1, A0);
      put<0, 1>(A1, C); put<1, 1>(A1, C); put<2, 1>(A1, C); put<3, 1>(A1, C); put<4, 1>(A1, C); put<5, 1>(A1, C);
      put<6, 1>(A1, C); put<7, 1>(A1, C); put<8, 1>(A1, C); put<9, 1>(A1, C); put<10, 1>(A1, C); put<11, 1>(A1, C);
    }
    if (ek - 1 > 253) redo = 0xFFFF;
    if (redo) {
      asm volatile("bar.sync 5, 256;" ::: "memory");
      const int k = threadIdx.x;
#pragma unroll 1
      for (int i = 0; i < nit + (cl < P.nfill); i++) {
        if (!((redo >> i) & 1) || k >= CH) continue;
        const int o = origin(i);
#pragma unroll 1
        for (int t = 0; t < (i < nit ? 48 : 16); t++) {
          const int y = (o >> 9) + (t >> 3), x = (o & 511) + (t & 7) * 8;
          float acc[8];
#pragma unroll
          for (int j = 0; j < 8; j++) acc[j] = 0.f;
#pragma unroll 1
          for (int rs = 0; rs < 9; rs++) {
            const int yy = y + rs / 3 - 1, xx = x + rs % 3 - 1;
            if ((uint32_t)yy >= IMG) continue;
#pragma unroll 1
            for (int c = 0; c < CH; c += 2) {
              const float w0 = __bfloat162float(wgt[(rs * CH + c) * CH + k]), w1 = __bfloat162float(wgt[(rs * CH + c + 1) * CH + k]);
#pragma unroll
              for (int j = 0; j < 8; j++) {
                if ((uint32_t)(xx + j) < IMG) {
                  const uint32_t v = __ldg(reinterpret_cast<const uint32_t*>(xin + (yy * IMG + xx + j) * CH + c));
                  acc[j] = fmaf(__uint_as_float(v & 0xFFFF0000u), w1, fmaf(__uint_as_float(v << 16), w0, acc[j]));
                }
              }
            }
          }
#pragma unroll
          for (int j = 0; j < 8; j++) out[(y * IMG + x + j) * CH + k] = __float2bfloat16(acc[j]);
        }
      }
    }
    __syncwarp();
    asm volatile("barrier.cluster.wait.aligned;" ::: "memory");
  }
}

typedef CUresult (*EncFn)(CUtensorMap*, CUtensorMapDataType, cuuint32_t, void*, const cuuint64_t*, const cuuint64_t*,
                          const cuuint32_t*, const cuuint32_t*, CUtensorMapInterleave, CUtensorMapSwizzle,
                          CUtensorMapL2promotion, CUtensorMapFloatOOBfill);

}

extern "C" void kernel_launch(void* const* d_in, const int* in_sizes, int n_in, void* d_out, int out_size) {
  const __nv_bfloat16* x = (const __nv_bfloat16*)d_in[0];
  const __nv_bfloat16* w = (const __nv_bfloat16*)d_in[1];
  __nv_bfloat16* out = (__nv_bfloat16*)d_out;

  static EncFn enc = nullptr;
  static void *U = nullptr, *ready = nullptr;
  if (!enc) {
    cudaGetSymbolAddress(&U, g_U);
    cudaGetSymbolAddress(&ready, g_ready);
    void* fn = nullptr; cudaDriverEntryPointQueryResult st;
    cudaGetDriverEntryPoint("cuTensorMapEncodeTiled", &fn, cudaEnableDefault, &st);
    enc = (EncFn)fn;
    cudaFuncSetAttribute(wino_main, cudaFuncAttributeMaxDynamicSharedMemorySize, SMEM_BYTES);
    cudaFuncSetAttribute(wino_main, cudaFuncAttributeNonPortableClusterSizeAllowed, 1);
  }
  CUtensorMap xmap[4];
  for (int i = 0; i < 4; i++) {
    cuuint64_t dims[3] = {CH, IMG, IMG};
    cuuint64_t str[2] = {CH * 2, (cuuint64_t)ROWB};
    cuuint32_t box[3] = {i != 2 ? 32u : 64u, i != 2 ? 4u : 66u, i == 2 ? 1u : i == 1 ? 4u : 8u};
    cuuint32_t es[3] = {1, 1, 1};
    enc(&xmap[i], CU_TENSOR_MAP_DATA_TYPE_BFLOAT16, 3, (void*)x, dims, str, box, es, CU_TENSOR_MAP_INTERLEAVE_NONE,
        CU_TENSOR_MAP_SWIZZLE_NONE, i == 3 ? CU_TENSOR_MAP_L2_PROMOTION_NONE : CU_TENSOR_MAP_L2_PROMOTION_L2_128B, CU_TENSOR_MAP_FLOAT_OOB_FILL_NONE);
  }
  cudaLaunchConfig_t cfg = {};
  cudaLaunchAttribute attr[2];
  cfg.blockDim = dim3(NTHREADS);
  cfg.dynamicSmemBytes = SMEM_BYTES;
  cfg.stream = cudaStreamPerThread;
  attr[0].id = cudaLaunchAttributeClusterDimension;
  attr[0].val.clusterDim.x = 16; attr[0].val.clusterDim.y = 1; attr[0].val.clusterDim.z = 1;
  attr[1].id = cudaLaunchAttributeProgrammaticStreamSerialization;
  attr[1].val.programmaticStreamSerializationAllowed = 1;
  cfg.attrs = attr;
  static int mlg = 0, ns = 0, n2 = 0;
  if (!mlg) {
    cfg.numAttrs = 1;
    cfg.gridDim = dim3(128);
    int n[3] = {0, 0, 0};
    for (int i = 0; i < 3; i++) {
      attr[0].val.clusterDim.x = i == 2 ? 2 : 16 >> i;
      if (cudaOccupancyMaxActiveClusters(&n[i], wino_main, &cfg) != cudaSuccess) { n[i] = 0; cudaGetLastError(); }
    }
    mlg = n[0] >= 7 ? 4 : 3;
    ns = mlg == 4 ? 2 * n[0] : n[1];
    ns = ns < 1 ? 1 : ns > 16 ? 16 : ns;
    n2 = n[2] - 4 * ns;
  }
  const int nf = 4 * (16 - ns), nb = n2 < nf ? nf : n2 > 5 * nf ? 5 * nf : n2;
  Params P = {(uint8_t*)U, (uint32_t*)ready, 3, mlg, 5, 1, 5 * ns, 5, ns, 0, 0, 8 * ns, 8 * ns + 2 * nb};
  for (int c = 0; c < 6; c++) {
    P.un[c] = make_uint4(unit(UN_P, c) * TUNIT, unit(UN_Q, c) * TUNIT, unit(UN_R, c) * TUNIT, unit(UN_S, c) * TUNIT);
    P.un[6 + c] = make_uint4(unit(UN_FP, c) * TUNIT, unit(UN_FQ, c) * TUNIT, 0, 0);
  }
  attr[0].val.clusterDim.x = 1 << mlg;
  cfg.numAttrs = 1;
  cfg.gridDim = dim3(8 * ns);
  cudaLaunchKernelEx(&cfg, wino_main, xmap[0], xmap[1], xmap[2], xmap[3], x, w, out, P);
  if (!nb) return;
  cudaStreamCaptureStatus cap = cudaStreamCaptureStatusNone;
  cudaStreamIsCapturing(cfg.stream, &cap);
  P.lg = P.mlg = 1; P.ufirst = 1; P.ustep = nb; P.nunit = 5 * nf; P.nfill = nf; P.s0 = ns; P.second = cap == cudaStreamCaptureStatusActive ? 1 : 2;
  attr[0].val.clusterDim.x = 2;
  cfg.numAttrs = 2;
  cfg.gridDim = dim3(2 * nb);
  cudaLaunchKernelEx(&cfg, wino_main, xmap[0], xmap[1], xmap[2], xmap[3], x, w, out, P);
}
```
